```python
import torch

def _softmax(x, axis=-1):
    return torch.softmax(x, dim=axis)
def _gelu(x):
    return torch.nn.functional.gelu(x, approximate="tanh")
def _silu(x):
    return torch.nn.functional.silu(x)
def _sigmoid(x):
    return torch.sigmoid(x)
def _layernorm(x, axis=-1, eps=1e-5):
    m = x.mean(dim=axis, keepdim=True)
    v = x.var(dim=axis, keepdim=True, unbiased=False)
    return (x - m) / torch.sqrt(v + eps)
def _scatter_add(tgt, idx, src, axis=0):
    return tgt.clone().index_add_(axis, idx, src)
def _segment_sum(src, seg, n):
    out = torch.zeros((n,) + src.shape[1:], dtype=src.dtype)
    return out.index_add_(0, seg, src)
def _pad(x, pw):
    flat = tuple(v for pair in reversed(pw) for v in pair)
    return torch.nn.functional.pad(x, flat)

kernel_name = 'concat_heads__linear_attn_block__softmax_full_mha__prompt'

def setup_inputs():

    _w = (lambda a: (lambda t: t.to(torch.bfloat16) if t.is_floating_point() else t)(torch.as_tensor(a)))
    def _A_setup():
        B, S, D = 1, 2048, 448
        return {
            "x": _w((lambda *s: torch.randn(*s, dtype=torch.bfloat16) * 0.05)(B, S, D)),
            "wqkv": _w((lambda *s: torch.randn(*s, dtype=torch.bfloat16) * 1.6)(D, 3 * D)),
            "wo": _w((lambda *s: torch.randn(*s, dtype=torch.bfloat16) * 0.05)(D, D)),
        }
    _A_in = _A_setup()

    def _B_setup():
        B, S, D = 1, 2048, 448
        return {
            "x": _w((lambda *s: torch.randn(*s, dtype=torch.bfloat16) * 0.2)(B, S, D)),
            "wqkv": _w((lambda *s: torch.randn(*s, dtype=torch.bfloat16) * 0.2)(D, 3 * D)),
            "wo": _w((lambda *s: torch.randn(*s, dtype=torch.bfloat16) * 0.05)(D, D)),
        }
    _B_in = _B_setup()

    return {
        "A_x": _A_in["x"],
        "A_wqkv": _A_in["wqkv"],
        "A_wo": _A_in["wo"],
        "B_x": _B_in["x"],
        "B_wqkv": _B_in["wqkv"],
        "B_wo": _B_in["wo"],
    }

def reference(A_x, A_wqkv, A_wo, B_x, B_wqkv, B_wo):
    def _A_ref(x, wqkv, wo):
        B, S, D = x.shape
        H = 16; Dh = D // H
        qkv = (lambda x, *d: x.permute(*d))((x @ wqkv).reshape(B, S, 3, H, Dh), 2, 0, 3, 1, 4)
        q, k, v = qkv[0], qkv[1], qkv[2]
        phi = lambda t: torch.where(t > 0, t + 1, torch.exp(t)) + 1e-6
        pq, pk = phi(q), phi(k)
        kv = torch.einsum("bhsd,bhse->bhde", pk, v)
        z = torch.einsum("bhsd->bhd", pk)
        num = torch.einsum("bhqd,bhde->bhqe", pq, kv)
        den = torch.einsum("bhqd,bhd->bhq", pq, z)[..., None] + 1e-6
        o = num / den
        return (lambda x, *d: x.permute(*d))(o, 0, 2, 1, 3).reshape(B, S, D) @ wo

    def _B_ref(x, wqkv, wo):
        B, S, D = x.shape
        H = 16; Dh = D // H
        qkv = (lambda x, *d: x.permute(*d))((x @ wqkv).reshape(B, S, 3, H, Dh), 2, 0, 3, 1, 4)
        q, k, v = qkv[0], qkv[1], qkv[2]
        scale = Dh ** -0.5
        scores = torch.einsum("bhqd,bhkd->bhqk", q, k) * scale
        p = _softmax(scores, axis=-1)
        o = torch.einsum("bhqk,bhkd->bhqd", p, v)
        return (lambda x, *d: x.permute(*d))(o, 0, 2, 1, 3).reshape(B, S, D) @ wo

    a = _A_ref(A_x, A_wqkv, A_wo)
    b = _B_ref(B_x, B_wqkv, B_wo)
    return torch.concatenate([a, b], axis=-1)
```

```cpp
#include <cuda_runtime.h>
#include <cuda_bf16.h>
#include <cuda_fp16.h>
#include <cuda.h>
#include <stdint.h>

namespace {

constexpr int S_LEN = 2048, DM = 448, DH = 28;
constexpr float QSCALE = 0.18898223650461362f * 1.4426950408889634f;

constexpr uint32_t SM_KV = 0;
constexpr uint32_t SM_H = 32768;
constexpr uint32_t H_STAGE = 40960;
constexpr uint32_t SM_XA = 65536;
constexpr uint32_t SM_WA = 180224;
constexpr uint32_t SM_STG = 212992;
constexpr uint32_t SM_BAR = 229376;
constexpr uint32_t SM_STAT = SM_BAR + 512;
constexpr uint32_t SM_ORDER = SM_STAT + 16;
constexpr uint32_t SMEM_BYTES = SM_BAR + 2048 + 1024;

enum {
  B_FULLH = 0, B_EMPTYH = 4, B_FULLKV = 7, B_EMPTYKV = 11, B_OWNRDY = 15, B_STOREDONE = 16, B_STOREDONE1 = 17,
  B_FULLXA = 18, B_FULLWA = 25, B_EMPTYWA = 29, B_XAFREE = 33, B_STGFREE = 34, B_STATS = 35, B_ATTNDONE = 36,
  B_FULLWOB = 37, B_LOOPDONE = 38, B_PUBA = 39, B_EMPTYXA = 40, B_FULLOB = 47, B_H3FREE = 55, B_COUNT = 56
};

enum { F_KV = 0, F_OA = 256, F_OB = 384, F_COUNT = 512 };
__device__ __align__(1024) __half g_kv[16 * S_LEN * 64];
__device__ __align__(1024) __nv_bfloat16 g_oA[S_LEN * 512];
__device__ __align__(1024) __nv_bfloat16 g_oB[S_LEN * 512];
__device__ __align__(1024) uint4 g_part[8 * 16 * 56 * 32];
__device__ __align__(1024) uint2 g_kvf[8 * 64 * 32];
__device__ __align__(1024) unsigned long long g_stats[8 * 64 * 2];
__device__ __align__(1024) unsigned g_flags[F_COUNT];
__device__ unsigned g_epoch = 1;
#define TSTAMP(i) do {} while (0)
#define GSTAMP(i) do {} while (0)
#define TDUMP() do {} while (0)
#define ISTAMP(i, v) do {} while (0)

struct __align__(64) Params {
  CUtensorMap xB, wBh, xA, wA, woA, woB, kv, oA, oB, outs;
  const __nv_bfloat16* xBp;
  const __nv_bfloat16* wBp;
  uint4* part;
  uint2* kvf;
  unsigned long long* stats;
  unsigned* flags;
  unsigned* epoch;
  int force_slow;
  uint32_t zero;
};

constexpr uint32_t SPIN_LIMIT = 1u << 24;
#define AWAIT 3
#define AFLY 2
#define AGRP 2
constexpr bool A_ON = true;

__device__ __forceinline__ void trap_now() { asm volatile("st.global.u32 [%0], %1;" ::"l"(0ull), "r"(0) : "memory"); }
__device__ __forceinline__ void mbar_init(uint32_t a, uint32_t c) {
  asm volatile("mbarrier.init.shared::cta.b64 [%0], %1;" ::"r"(a), "r"(c));
}
__device__ __forceinline__ void mbar_expect(uint32_t a, uint32_t bytes) {
  asm volatile("mbarrier.arrive.expect_tx.shared::cta.b64 _, [%0], %1;" ::"r"(a), "r"(bytes) : "memory");
}
__device__ __forceinline__ void mbar_arrive(uint32_t a) {
  asm volatile("mbarrier.arrive.shared::cta.b64 _, [%0];" ::"r"(a) : "memory");
}
__device__ __forceinline__ void mbar_arrive_if(uint32_t a, bool c) {
  asm volatile("{\n.reg .pred p;\nsetp.ne.b32 p, %1, 0;\n@p mbarrier.arrive.shared::cta.b64 _, [%0];\n}" ::"r"(a),
               "r"((uint32_t)c) : "memory");
}
__device__ __forceinline__ void mbar_arrive_cluster_if(uint32_t a, bool c) {
  asm volatile("{\n.reg .pred p;\nsetp.ne.b32 p, %1, 0;\n@p mbarrier.arrive.shared::cluster.b64 _, [%0];\n}" ::"r"(a),
               "r"((uint32_t)c) : "memory");
}
__device__ __forceinline__ uint32_t mbar_test(uint32_t a, uint32_t parity) {
  uint32_t ok;
  asm volatile("{\n.reg .pred p;\nmbarrier.test_wait.parity.shared::cta.b64 p, [%1], %2;\nselp.u32 %0, 1, 0, p;\n}"
               : "=r"(ok) : "r"(a), "r"(parity) : "memory");
  return ok;
}
__device__ __forceinline__ void mbar_wait(uint32_t a, uint32_t parity, uint32_t have = 0) {
  asm volatile(
      "{\n.reg .pred p;\nsetp.ne.u32 p, %2, 0;\n@p bra.uni DONE;\n"
      "SPIN:\nmbarrier.try_wait.parity.shared::cta.b64 p, [%0], %1;\n@!p bra.uni SPIN;\nDONE:\n}"
      ::"r"(a), "r"(parity), "r"(have) : "memory");
}
__device__ __forceinline__ uint32_t mapa(uint32_t a, uint32_t rank) {
  uint32_t r;
  asm("mapa.shared::cluster.u32 %0, %1, %2;" : "=r"(r) : "r"(a), "r"(rank));
  return r;
}
__device__ __forceinline__ bool elect() {
  uint32_t p;
  asm volatile("{\n.reg .pred P;\nelect.sync _|P, 0xffffffff;\nselp.u32 %0, 1, 0, P;\n}" : "=r"(p));
  return p;
}
__device__ __forceinline__ void tma_load(uint32_t dst, const CUtensorMap* m, int c0, int c1, uint32_t bar) {
  asm volatile("cp.async.bulk.tensor.2d.shared::cluster.global.mbarrier::complete_tx::bytes [%0], [%1, {%3, %4}], [%2];"
               ::"r"(dst), "l"(m), "r"(bar), "r"(c0), "r"(c1) : "memory");
}
__device__ __forceinline__ void tma_load_mc(uint32_t dst, const CUtensorMap* m, int c0, int c1, uint32_t bar) {
  asm volatile(
      "cp.async.bulk.tensor.2d.shared::cluster.global.mbarrier::complete_tx::bytes.multicast::cluster [%0], [%1, {%3, %4}], [%2], %5;"
      ::"r"(dst), "l"(m), "r"(bar), "r"(c0), "r"(c1), "h"((uint16_t)3) : "memory");
}
__device__ __forceinline__ void tma_store(const CUtensorMap* m, int c0, int c1, uint32_t src) {
  asm volatile("cp.async.bulk.tensor.2d.global.shared::cta.bulk_group [%0, {%2, %3}], [%1];" ::"l"(m), "r"(src),
               "r"(c0), "r"(c1) : "memory");
}
__device__ __forceinline__ void tma_prefetch_l2(const CUtensorMap* m, int c0, int c1) {
  asm volatile("cp.async.bulk.prefetch.tensor.2d.L2.global [%0, {%1, %2}];" ::"l"(m), "r"(c0), "r"(c1) : "memory");
}
__device__ __forceinline__ void prefetch_map(const CUtensorMap* m) {
  asm volatile("prefetch.tensormap [%0];" ::"l"(m) : "memory");
}
__device__ __forceinline__ void fence_async_smem() { asm volatile("fence.proxy.async.shared::cta;" ::: "memory"); }
__device__ __forceinline__ void fence_async_all() { asm volatile("fence.proxy.async.global;" ::: "memory"); }
__device__ __forceinline__ void named_sync(int id, int n) { asm volatile("bar.sync %0, %1;" ::"r"(id), "r"(n) : "memory"); }
__device__ __forceinline__ bool named_or(int id, int n, bool v) {
  uint32_t r;
  asm volatile("{\n.reg .pred p, q;\nsetp.ne.b32 p, %3, 0;\nbarrier.red.or.pred q, %1, %2, p;\nselp.u32 %0, 1, 0, q;\n}"
               : "=r"(r) : "r"(id), "r"(n), "r"((uint32_t)v) : "memory");
  return r;
}
__device__ __forceinline__ unsigned ld_flag(const unsigned* p) {
  unsigned v;
  asm volatile("ld.relaxed.gpu.global.u32 %0, [%1];" : "=r"(v) : "l"(p) : "memory");
  return v;
}
__device__ __forceinline__ void bulk_commit() { asm volatile("cp.async.bulk.commit_group;" ::: "memory"); }
__device__ __forceinline__ void bulk_wait() {
  asm volatile("cp.async.bulk.wait_group 0;" ::: "memory");
  asm volatile("fence.proxy.async.global;" ::: "memory");
}
__device__ __forceinline__ void st_release(unsigned* p, unsigned v) {
  asm volatile("st.release.gpu.global.u32 [%0], %1;" ::"l"(p), "r"(v) : "memory");
}
__device__ __forceinline__ void poll_flags(const unsigned* flags, int n, unsigned tag, int lane) {
  uint32_t it = 0;
  while (true) {
    bool ok = lane >= n || ld_flag(flags + lane) == tag;
    if (__all_sync(0xffffffffu, ok)) break;
    if (++it > SPIN_LIMIT) trap_now();
  }
  __syncwarp();
}

__device__ __forceinline__ void poll_tags(const unsigned* w, unsigned tag) {
  uint32_t it = 0;
  while (!__all_sync(0xffffffffu, ld_flag(w) == tag)) {
    if (++it > SPIN_LIMIT) trap_now();
    __nanosleep(300);
  }
}
__device__ __forceinline__ void wg_fence() { asm volatile("wgmma.fence.sync.aligned;" ::: "memory"); }
__device__ __forceinline__ void wg_commit() { asm volatile("wgmma.commit_group.sync.aligned;" ::: "memory"); }
template <int N> __device__ __forceinline__ void wg_wait() { asm volatile("wgmma.wait_group.sync.aligned %0;" ::"n"(N) : "memory"); }
template <int N> __device__ __forceinline__ void pin(float (&a)[N]) {
#pragma unroll
  for (int i = 0; i < N; i++) asm volatile("" : "+f"(a[i])::"memory");
}
template <int N> __device__ __forceinline__ void pin(uint32_t (&a)[N]) {
#pragma unroll
  for (int i = 0; i < N; i++) asm volatile("" : "+r"(a[i])::"memory");
}
__device__ __forceinline__ uint64_t desc(uint32_t lo) { return (uint64_t)0x40000040u << 32 | lo; }
__device__ __forceinline__ uint32_t desc_lo(uint32_t addr, uint32_t lbo) { return ((addr & 0x3FFFF) >> 4) | ((lbo >> 4) << 16); }

__device__ __forceinline__ void stsm4(uint32_t addr, uint32_t r0, uint32_t r1, uint32_t r2, uint32_t r3) {
  asm volatile("stmatrix.sync.aligned.m8n8.x4.shared.b16 [%0], {%1, %2, %3, %4};" ::"r"(addr), "r"(r0), "r"(r1),
               "r"(r2), "r"(r3) : "memory");
}
__device__ __forceinline__ void stsm2(uint32_t addr, uint32_t r0, uint32_t r1) {
  asm volatile("stmatrix.sync.aligned.m8n8.x2.shared.b16 [%0], {%1, %2};" ::"r"(addr), "r"(r0), "r"(r1) : "memory");
}
__device__ __forceinline__ void stage56(uint32_t base, const uint32_t (&v)[14], int lane) {
  const uint32_t a = base + (lane & 15) * 112 + (lane >> 4) * 16;
  stsm4(a, v[0], v[1], v[2], v[3]);
  stsm4(a + 32, v[4], v[5], v[6], v[7]);
  stsm4(a + 64, v[8], v[9], v[10], v[11]);
  stsm2(a + 96, v[12], v[13]);
}
__device__ __forceinline__ void stage64(uint32_t base, const uint32_t (&v)[14], int lane, int off) {
  const uint32_t a = base + (lane & 15) * 128, c = off + (lane >> 4), x = lane & 7;
  stsm4(a + ((c ^ x) << 4), v[0], v[1], v[2], v[3]);
  stsm4(a + (((c + 2) ^ x) << 4), v[4], v[5], v[6], v[7]);
  stsm4(a + (((c + 4) ^ x) << 4), v[8], v[9], v[10], v[11]);
  stsm4(a + ((((c + 6) & 7) ^ x) << 4), v[12], v[13], 0, 0);
}
__device__ __forceinline__ uint32_t pack_h(float lo, float hi) {
  uint32_t r;
  asm("cvt.rn.f16x2.f32 %0, %1, %2;" : "=r"(r) : "f"(hi), "f"(lo));
  return r;
}
__device__ __forceinline__ uint32_t pack_b(float lo, float hi) {
  uint32_t r;
  asm("cvt.rn.bf16x2.f32 %0, %1, %2;" : "=r"(r) : "f"(hi), "f"(lo));
  return r;
}
__device__ __forceinline__ uint32_t ex2_h2(uint32_t x) {
  uint32_t y;
  asm("ex2.approx.f16x2 %0, %1;" : "=r"(y) : "r"(x));
  return y;
}
__device__ __forceinline__ float ex2_f(float x) {
  float y;
  asm("ex2.approx.ftz.f32 %0, %1;" : "=f"(y) : "f"(x));
  return y;
}
__device__ __forceinline__ float rcp_f(float x) {
  float y;
  asm("rcp.approx.f32 %0, %1;" : "=f"(y) : "f"(x));
  return y;
}
__device__ __forceinline__ uint32_t hfma2(uint32_t a, uint32_t b, uint32_t c) {
  uint32_t y;
  asm("fma.rn.f16x2 %0, %1, %2, %3;" : "=r"(y) : "r"(a), "r"(b), "r"(c));
  return y;
}
__device__ __forceinline__ uint32_t habsmax2(uint32_t m, uint32_t a) {
  uint32_t y;
  asm("max.f16x2 %0, %1, %2;" : "=r"(y) : "r"(m), "r"(a & 0x7fff7fffu));
  return y;
}
__device__ __forceinline__ float h_lo(uint32_t v) { return __half2float(__ushort_as_half((unsigned short)(v & 0xffff))); }
__device__ __forceinline__ float h_hi(uint32_t v) { return __half2float(__ushort_as_half((unsigned short)(v >> 16))); }
__device__ __forceinline__ uint32_t phi2(float a, float b) {
  const float ea = ex2_f(fminf(a * 1.4426950408889634f, 0.f)), eb = ex2_f(fminf(b * 1.4426950408889634f, 0.f));
  return pack_b(fmaxf(a, 0.f) + ea + 1e-6f, fmaxf(b, 0.f) + eb + 1e-6f);
}

__device__ __forceinline__ void mma_n192_ss_tb(float (&d)[96], uint64_t a, uint64_t b, int acc) {
  asm volatile("{\n.reg .pred p;\nsetp.ne.b32 p, %98, 0;\n"
    "wgmma.mma_async.sync.aligned.m64n192k16.f32.bf16.bf16 "
    "{%0,%1,%2,%3,%4,%5,%6,%7,%8,%9,%10,%11,%12,%13,%14,%15,%16,%17,%18,%19,%20,%21,%22,%23,%24,%25,%26,%27,%28,%29,%30,%31,%32,%33,%34,%35,%36,%37,%38,%39,%40,%41,%42,%43,%44,%45,%46,%47,%48,%49,%50,%51,%52,%53,%54,%55,%56,%57,%58,%59,%60,%61,%62,%63,%64,%65,%66,%67,%68,%69,%70,%71,%72,%73,%74,%75,%76,%77,%78,%79,%80,%81,%82,%83,%84,%85,%86,%87,%88,%89,%90,%91,%92,%93,%94,%95}, "
    "%96, %97, p, 1, 1, 0, 1;\n}\n"
    : "+f"(d[0]), "+f"(d[1]), "+f"(d[2]), "+f"(d[3]), "+f"(d[4]), "+f"(d[5]), "+f"(d[6]), "+f"(d[7]),
      "+f"(d[8]), "+f"(d[9]), "+f"(d[10]), "+f"(d[11]), "+f"(d[12]), "+f"(d[13]), "+f"(d[14]), "+f"(d[15]),
      "+f"(d[16]), "+f"(d[17]), "+f"(d[18]), "+f"(d[19]), "+f"(d[20]), "+f"(d[21]), "+f"(d[22]), "+f"(d[23]),
      "+f"(d[24]), "+f"(d[25]), "+f"(d[26]), "+f"(d[27]), "+f"(d[28]), "+f"(d[29]), "+f"(d[30]), "+f"(d[31]),
      "+f"(d[32]), "+f"(d[33]), "+f"(d[34]), "+f"(d[35]), "+f"(d[36]), "+f"(d[37]), "+f"(d[38]), "+f"(d[39]),
      "+f"(d[40]), "+f"(d[41]), "+f"(d[42]), "+f"(d[43]), "+f"(d[44]), "+f"(d[45]), "+f"(d[46]), "+f"(d[47]),
      "+f"(d[48]), "+f"(d[49]), "+f"(d[50]), "+f"(d[51]), "+f"(d[52]), "+f"(d[53]), "+f"(d[54]), "+f"(d[55]),
      "+f"(d[56]), "+f"(d[57]), "+f"(d[58]), "+f"(d[59]), "+f"(d[60]), "+f"(d[61]), "+f"(d[62]), "+f"(d[63]),
      "+f"(d[64]), "+f"(d[65]), "+f"(d[66]), "+f"(d[67]), "+f"(d[68]), "+f"(d[69]), "+f"(d[70]), "+f"(d[71]),
      "+f"(d[72]), "+f"(d[73]), "+f"(d[74]), "+f"(d[75]), "+f"(d[76]), "+f"(d[77]), "+f"(d[78]), "+f"(d[79]),
      "+f"(d[80]), "+f"(d[81]), "+f"(d[82]), "+f"(d[83]), "+f"(d[84]), "+f"(d[85]), "+f"(d[86]), "+f"(d[87]),
      "+f"(d[88]), "+f"(d[89]), "+f"(d[90]), "+f"(d[91]), "+f"(d[92]), "+f"(d[93]), "+f"(d[94]), "+f"(d[95])
    : "l"(a), "l"(b), "r"(acc));
}
__device__ __forceinline__ void mma_qk(uint32_t (&d)[16], uint32_t a0, uint32_t a1, uint32_t a2, uint32_t a3, uint64_t b, int acc) {
  asm volatile("{\n.reg .pred p;\nsetp.ne.b32 p, %21, 0;\n"
    "wgmma.mma_async.sync.aligned.m64n64k16.f16.f16.f16 "
    "{%0,%1,%2,%3,%4,%5,%6,%7,%8,%9,%10,%11,%12,%13,%14,%15}, "
    "{%16,%17,%18,%19}, %20, p, 1, 1, 0;\n}\n"
    : "+r"(d[0]), "+r"(d[1]), "+r"(d[2]), "+r"(d[3]), "+r"(d[4]), "+r"(d[5]), "+r"(d[6]), "+r"(d[7]),
      "+r"(d[8]), "+r"(d[9]), "+r"(d[10]), "+r"(d[11]), "+r"(d[12]), "+r"(d[13]), "+r"(d[14]), "+r"(d[15])
    : "r"(a0), "r"(a1), "r"(a2), "r"(a3), "l"(b), "r"(acc));
}
__device__ __forceinline__ void mma_pv(float (&d)[16], uint32_t a0, uint32_t a1, uint32_t a2, uint32_t a3, uint64_t b, int acc) {
  asm volatile("{\n.reg .pred p;\nsetp.ne.b32 p, %21, 0;\n"
    "wgmma.mma_async.sync.aligned.m64n32k16.f32.f16.f16 "
    "{%0,%1,%2,%3,%4,%5,%6,%7,%8,%9,%10,%11,%12,%13,%14,%15}, "
    "{%16,%17,%18,%19}, %20, p, 1, 1, 1;\n}\n"
    : "+f"(d[0]), "+f"(d[1]), "+f"(d[2]), "+f"(d[3]), "+f"(d[4]), "+f"(d[5]), "+f"(d[6]), "+f"(d[7]),
      "+f"(d[8]), "+f"(d[9]), "+f"(d[10]), "+f"(d[11]), "+f"(d[12]), "+f"(d[13]), "+f"(d[14]), "+f"(d[15])
    : "r"(a0), "r"(a1), "r"(a2), "r"(a3), "l"(b), "r"(acc));
}
__device__ __forceinline__ void mma_pv_h(uint32_t (&d)[8], uint32_t a0, uint32_t a1, uint32_t a2, uint32_t a3, uint64_t b, int acc) {
  asm volatile("{\n.reg .pred p;\nsetp.ne.b32 p, %13, 0;\n"
    "wgmma.mma_async.sync.aligned.m64n32k16.f16.f16.f16 "
    "{%0,%1,%2,%3,%4,%5,%6,%7}, "
    "{%8,%9,%10,%11}, %12, p, 1, 1, 1;\n}\n"
    : "+r"(d[0]), "+r"(d[1]), "+r"(d[2]), "+r"(d[3]), "+r"(d[4]), "+r"(d[5]), "+r"(d[6]), "+r"(d[7])
    : "r"(a0), "r"(a1), "r"(a2), "r"(a3), "l"(b), "r"(acc));
}
__device__ __forceinline__ void mma_n128_ss_ta(float (&d)[64], uint64_t a, uint64_t b, int acc) {
  asm volatile("{\n.reg .pred p;\nsetp.ne.b32 p, %66, 0;\n"
    "wgmma.mma_async.sync.aligned.m64n128k16.f32.bf16.bf16 "
    "{%0,%1,%2,%3,%4,%5,%6,%7,%8,%9,%10,%11,%12,%13,%14,%15,%16,%17,%18,%19,%20,%21,%22,%23,%24,%25,%26,%27,%28,%29,%30,%31,%32,%33,%34,%35,%36,%37,%38,%39,%40,%41,%42,%43,%44,%45,%46,%47,%48,%49,%50,%51,%52,%53,%54,%55,%56,%57,%58,%59,%60,%61,%62,%63}, "
    "%64, %65, p, 1, 1, 1, 0;\n}\n"
    : "+f"(d[0]), "+f"(d[1]), "+f"(d[2]), "+f"(d[3]), "+f"(d[4]), "+f"(d[5]), "+f"(d[6]), "+f"(d[7]),
      "+f"(d[8]), "+f"(d[9]), "+f"(d[10]), "+f"(d[11]), "+f"(d[12]), "+f"(d[13]), "+f"(d[14]), "+f"(d[15]),
      "+f"(d[16]), "+f"(d[17]), "+f"(d[18]), "+f"(d[19]), "+f"(d[20]), "+f"(d[21]), "+f"(d[22]), "+f"(d[23]),
      "+f"(d[24]), "+f"(d[25]), "+f"(d[26]), "+f"(d[27]), "+f"(d[28]), "+f"(d[29]), "+f"(d[30]), "+f"(d[31]),
      "+f"(d[32]), "+f"(d[33]), "+f"(d[34]), "+f"(d[35]), "+f"(d[36]), "+f"(d[37]), "+f"(d[38]), "+f"(d[39]),
      "+f"(d[40]), "+f"(d[41]), "+f"(d[42]), "+f"(d[43]), "+f"(d[44]), "+f"(d[45]), "+f"(d[46]), "+f"(d[47]),
      "+f"(d[48]), "+f"(d[49]), "+f"(d[50]), "+f"(d[51]), "+f"(d[52]), "+f"(d[53]), "+f"(d[54]), "+f"(d[55]),
      "+f"(d[56]), "+f"(d[57]), "+f"(d[58]), "+f"(d[59]), "+f"(d[60]), "+f"(d[61]), "+f"(d[62]), "+f"(d[63])
    : "l"(a), "l"(b), "r"(acc));
}
__device__ __forceinline__ void mma_n64_rs(float (&d)[32], uint32_t a0, uint32_t a1, uint32_t a2, uint32_t a3, uint64_t b, int acc) {
  asm volatile("{\n.reg .pred p;\nsetp.ne.b32 p, %37, 0;\n"
    "wgmma.mma_async.sync.aligned.m64n64k16.f32.bf16.bf16 "
    "{%0,%1,%2,%3,%4,%5,%6,%7,%8,%9,%10,%11,%12,%13,%14,%15,%16,%17,%18,%19,%20,%21,%22,%23,%24,%25,%26,%27,%28,%29,%30,%31}, "
    "{%32,%33,%34,%35}, %36, p, 1, 1, 0;\n}\n"
    : "+f"(d[0]), "+f"(d[1]), "+f"(d[2]), "+f"(d[3]), "+f"(d[4]), "+f"(d[5]), "+f"(d[6]), "+f"(d[7]),
      "+f"(d[8]), "+f"(d[9]), "+f"(d[10]), "+f"(d[11]), "+f"(d[12]), "+f"(d[13]), "+f"(d[14]), "+f"(d[15]),
      "+f"(d[16]), "+f"(d[17]), "+f"(d[18]), "+f"(d[19]), "+f"(d[20]), "+f"(d[21]), "+f"(d[22]), "+f"(d[23]),
      "+f"(d[24]), "+f"(d[25]), "+f"(d[26]), "+f"(d[27]), "+f"(d[28]), "+f"(d[29]), "+f"(d[30]), "+f"(d[31])
    : "r"(a0), "r"(a1), "r"(a2), "r"(a3), "l"(b), "r"(acc));
}
__device__ __forceinline__ void mma_n64_rs_tb(float (&d)[32], uint32_t a0, uint32_t a1, uint32_t a2, uint32_t a3, uint64_t b, int acc) {
  asm volatile("{\n.reg .pred p;\nsetp.ne.b32 p, %37, 0;\n"
    "wgmma.mma_async.sync.aligned.m64n64k16.f32.bf16.bf16 "
    "{%0,%1,%2,%3,%4,%5,%6,%7,%8,%9,%10,%11,%12,%13,%14,%15,%16,%17,%18,%19,%20,%21,%22,%23,%24,%25,%26,%27,%28,%29,%30,%31}, "
    "{%32,%33,%34,%35}, %36, p, 1, 1, 1;\n}\n"
    : "+f"(d[0]), "+f"(d[1]), "+f"(d[2]), "+f"(d[3]), "+f"(d[4]), "+f"(d[5]), "+f"(d[6]), "+f"(d[7]),
      "+f"(d[8]), "+f"(d[9]), "+f"(d[10]), "+f"(d[11]), "+f"(d[12]), "+f"(d[13]), "+f"(d[14]), "+f"(d[15]),
      "+f"(d[16]), "+f"(d[17]), "+f"(d[18]), "+f"(d[19]), "+f"(d[20]), "+f"(d[21]), "+f"(d[22]), "+f"(d[23]),
      "+f"(d[24]), "+f"(d[25]), "+f"(d[26]), "+f"(d[27]), "+f"(d[28]), "+f"(d[29]), "+f"(d[30]), "+f"(d[31])
    : "r"(a0), "r"(a1), "r"(a2), "r"(a3), "l"(b), "r"(acc));
}
__device__ __forceinline__ void mma_n64_ss_tb(float (&d)[32], uint64_t a, uint64_t b, int acc) {
  asm volatile("{\n.reg .pred p;\nsetp.ne.b32 p, %34, 0;\n"
    "wgmma.mma_async.sync.aligned.m64n64k16.f32.bf16.bf16 "
    "{%0,%1,%2,%3,%4,%5,%6,%7,%8,%9,%10,%11,%12,%13,%14,%15,%16,%17,%18,%19,%20,%21,%22,%23,%24,%25,%26,%27,%28,%29,%30,%31}, "
    "%32, %33, p, 1, 1, 0, 1;\n}\n"
    : "+f"(d[0]), "+f"(d[1]), "+f"(d[2]), "+f"(d[3]), "+f"(d[4]), "+f"(d[5]), "+f"(d[6]), "+f"(d[7]),
      "+f"(d[8]), "+f"(d[9]), "+f"(d[10]), "+f"(d[11]), "+f"(d[12]), "+f"(d[13]), "+f"(d[14]), "+f"(d[15]),
      "+f"(d[16]), "+f"(d[17]), "+f"(d[18]), "+f"(d[19]), "+f"(d[20]), "+f"(d[21]), "+f"(d[22]), "+f"(d[23]),
      "+f"(d[24]), "+f"(d[25]), "+f"(d[26]), "+f"(d[27]), "+f"(d[28]), "+f"(d[29]), "+f"(d[30]), "+f"(d[31])
    : "l"(a), "l"(b), "r"(acc));
}
__device__ __forceinline__ void mma_n112_ss_tb(float (&d)[56], uint64_t a, uint64_t b, int acc) {
  asm volatile("{\n.reg .pred p;\nsetp.ne.b32 p, %58, 0;\n"
    "wgmma.mma_async.sync.aligned.m64n112k16.f32.bf16.bf16 "
    "{%0,%1,%2,%3,%4,%5,%6,%7,%8,%9,%10,%11,%12,%13,%14,%15,%16,%17,%18,%19,%20,%21,%22,%23,%24,%25,%26,%27,%28,%29,%30,%31,%32,%33,%34,%35,%36,%37,%38,%39,%40,%41,%42,%43,%44,%45,%46,%47,%48,%49,%50,%51,%52,%53,%54,%55}, "
    "%56, %57, p, 1, 1, 0, 1;\n}\n"
    : "+f"(d[0]), "+f"(d[1]), "+f"(d[2]), "+f"(d[3]), "+f"(d[4]), "+f"(d[5]), "+f"(d[6]), "+f"(d[7]),
      "+f"(d[8]), "+f"(d[9]), "+f"(d[10]), "+f"(d[11]), "+f"(d[12]), "+f"(d[13]), "+f"(d[14]), "+f"(d[15]),
      "+f"(d[16]), "+f"(d[17]), "+f"(d[18]), "+f"(d[19]), "+f"(d[20]), "+f"(d[21]), "+f"(d[22]), "+f"(d[23]),
      "+f"(d[24]), "+f"(d[25]), "+f"(d[26]), "+f"(d[27]), "+f"(d[28]), "+f"(d[29]), "+f"(d[30]), "+f"(d[31]),
      "+f"(d[32]), "+f"(d[33]), "+f"(d[34]), "+f"(d[35]), "+f"(d[36]), "+f"(d[37]), "+f"(d[38]), "+f"(d[39]),
      "+f"(d[40]), "+f"(d[41]), "+f"(d[42]), "+f"(d[43]), "+f"(d[44]), "+f"(d[45]), "+f"(d[46]), "+f"(d[47]),
      "+f"(d[48]), "+f"(d[49]), "+f"(d[50]), "+f"(d[51]), "+f"(d[52]), "+f"(d[53]), "+f"(d[54]), "+f"(d[55])
    : "l"(a), "l"(b), "r"(acc));
}
__device__ __forceinline__ void mma_n56_ss_tb(float (&d)[28], uint64_t a, uint64_t b, int acc) {
  asm volatile("{\n.reg .pred p;\nsetp.ne.b32 p, %30, 0;\n"
    "wgmma.mma_async.sync.aligned.m64n56k16.f32.bf16.bf16 "
    "{%0,%1,%2,%3,%4,%5,%6,%7,%8,%9,%10,%11,%12,%13,%14,%15,%16,%17,%18,%19,%20,%21,%22,%23,%24,%25,%26,%27}, "
    "%28, %29, p, 1, 1, 0, 1;\n}\n"
    : "+f"(d[0]), "+f"(d[1]), "+f"(d[2]), "+f"(d[3]), "+f"(d[4]), "+f"(d[5]), "+f"(d[6]), "+f"(d[7]),
      "+f"(d[8]), "+f"(d[9]), "+f"(d[10]), "+f"(d[11]), "+f"(d[12]), "+f"(d[13]), "+f"(d[14]), "+f"(d[15]),
      "+f"(d[16]), "+f"(d[17]), "+f"(d[18]), "+f"(d[19]), "+f"(d[20]), "+f"(d[21]), "+f"(d[22]), "+f"(d[23]),
      "+f"(d[24]), "+f"(d[25]), "+f"(d[26]), "+f"(d[27])
    : "l"(a), "l"(b), "r"(acc));
}

#define NPOLY 5
#define PGROUP 1
__device__ __forceinline__ uint32_t exp2_fma_h2(uint32_t x, uint32_t magic, uint32_t& chain) {
  uint32_t c, t, n, f;
  asm("min.xorsign.abs.f16x2 %0, %1, %2;" : "=r"(c) : "r"(x), "r"(0x4b004b00u));
  asm("add.rn.f16x2 %0, %1, %2;" : "=r"(t) : "r"(c), "r"(magic));
  asm("sub.rn.f16x2 %0, %1, %2;" : "=r"(n) : "r"(t), "r"(0x66006600u));
  asm("sub.rn.f16x2 %0, %1, %2;" : "=r"(f) : "r"(c), "r"(n));
  uint32_t q = hfma2(0x2af92af9u, f, 0x33be33beu);
  q = hfma2(q, f, 0x398c398cu);
  q = hfma2(q, f, 0x3c003c00u);
  chain = q;
  return q + (t << 10) - 0x01980000u;
}
__device__ __forceinline__ void exp_tile(const uint32_t (&s)[16], uint32_t (&p)[16], uint32_t zero, uint32_t& chain) {
  uint32_t magic = 0x66006600u;
#pragma unroll
  for (int i = 0; i < 16; i++) {
    const int k = i * NPOLY / 16;
    if ((i + 1) * NPOLY / 16 != k) {
      if (k % PGROUP == 0) magic = hfma2(chain, zero, 0x66006600u);
      p[i] = exp2_fma_h2(s[i], magic, chain);
    } else {
      p[i] = ex2_h2(s[i]);
    }
  }
}

__device__ __forceinline__ void slow_project(const __nv_bfloat16* __restrict__ xrow, const __nv_bfloat16* __restrict__ wcol,
                                             float (&o)[DH]) {
#pragma unroll
  for (int d = 0; d < DH; d++) o[d] = 0.f;
#pragma unroll 1
  for (int k = 0; k < DM; k += 2) {
    __nv_bfloat162 xv = *reinterpret_cast<const __nv_bfloat162*>(xrow + k);
#pragma unroll
    for (int u = 0; u < 2; u++) {
      float x = u ? __high2float(xv) : __low2float(xv);
      const uint2* wp = reinterpret_cast<const uint2*>(wcol + (size_t)(k + u) * (3 * DM));
#pragma unroll
      for (int d = 0; d < DH / 4; d++) {
        uint2 w = __ldg(wp + d);
        o[4 * d + 0] = fmaf(x, __uint_as_float(w.x << 16), o[4 * d + 0]);
        o[4 * d + 1] = fmaf(x, __uint_as_float(w.x & 0xffff0000u), o[4 * d + 1]);
        o[4 * d + 2] = fmaf(x, __uint_as_float(w.y << 16), o[4 * d + 2]);
        o[4 * d + 3] = fmaf(x, __uint_as_float(w.y & 0xffff0000u), o[4 * d + 3]);
      }
    }
  }
#pragma unroll
  for (int d = 0; d < DH; d++) o[d] = __bfloat162float(__float2bfloat16(o[d]));
}

__device__ __forceinline__ void slow_attention(const __nv_bfloat16* __restrict__ x, const __nv_bfloat16* __restrict__ w,
                                            float* scratch, uint32_t* stage, int row0, int p, int t, int bar_id) {
  const int head = 2 * p + (t >> 6), row = row0 + (t & 63);
  float q[DH], acc[DH], tmp[DH];
  slow_project(x + (size_t)row * DM, w + head * DH, q);
  float m = -INFINITY, l = 0.f;
#pragma unroll
  for (int d = 0; d < DH; d++) acc[d] = 0.f;
  float* mine = scratch + t * (2 * DH + 1);
  const float* keys = scratch + (t >> 6) * 64 * (2 * DH + 1);
#pragma unroll 1
  for (int kb = 0; kb < S_LEN; kb += 64) {
#pragma unroll 1
    for (int part = 0; part < 2; part++) {
      slow_project(x + (size_t)(kb + (t & 63)) * DM, w + (part + 1) * DM + head * DH, tmp);
#pragma unroll
      for (int d = 0; d < DH; d++) mine[part * DH + d] = tmp[d];
    }
    named_sync(bar_id, 128);
#pragma unroll 1
    for (int j = 0; j < 64; j++) {
      const float* kr = keys + j * (2 * DH + 1);
      float s = 0.f;
#pragma unroll
      for (int d = 0; d < DH; d++) s = fmaf(q[d], kr[d], s);
      s *= 0.18898223650461362f;
      float mn = fmaxf(m, s);
      float a = __expf(m - mn), pj = __expf(s - mn);
      l = l * a + pj;
#pragma unroll
      for (int d = 0; d < DH; d++) acc[d] = fmaf(pj, kr[DH + d], acc[d] * a);
      m = mn;
    }
    named_sync(bar_id, 128);
  }
  float r = rcp_f(l);
#pragma unroll
  for (int d = 0; d < DH; d += 2) {
    const int w = (p == 7) * 4 + (t >> 6) * 14 + (d >> 1);
    stage[(t & 63) * 32 + (((w >> 2) ^ (t & 7)) << 2) + (w & 3)] = pack_b(acc[d] * r, acc[d + 1] * r);
  }
}

__global__ void __cluster_dims__(2, 1, 1) __launch_bounds__(512, 1) fused_kernel(const __grid_constant__ Params P) {
  extern __shared__ uint8_t smem_raw[];
  const uint32_t sb = __shfl_sync(0xffffffffu, ((uint32_t)__cvta_generic_to_shared(smem_raw) + 1023) & ~1023u, 0);
  const uint32_t bar = sb + SM_BAR;
  const int wg = __shfl_sync(0xffffffffu, threadIdx.x >> 7, 0);
  const int warp = __shfl_sync(0xffffffffu, (threadIdx.x >> 5) & 3, 0);
  const int lane = threadIdx.x & 31;
  const int rank = blockIdx.x & 1;
  const int cl = blockIdx.x >> 1;
  const int ci = cl & 7;
  const int p = cl >> 3;
  const int r = 2 * ci + rank;
  const int G = 4 * ci + (p >> 1);
  const int cg = 2 * (p & 1) + rank;
  const int wcol = 56 * p - 8 * (p & 1);

  if (threadIdx.x == 0) { TSTAMP(0); GSTAMP(30); }
  unsigned tag;
  if (wg == 3) {
    asm volatile("setmaxnreg.dec.sync.aligned.u32 40;");
    auto head_x = [&](int c) {
      const uint32_t fb = bar + 8 * (B_FULLH + (c & 3));
      mbar_expect(fb, H_STAGE);
      tma_load(sb + SM_H + (c & 3) * H_STAGE, &P.xB, c * 64, r * 128, fb);
    };
    if (warp == 0) {
      if (elect()) {
        prefetch_map(&P.xB);
        prefetch_map(&P.wBh);
#pragma unroll
        for (int i = 0; i < 4; i++) mbar_init(bar + 8 * (B_FULLH + i), 1);
        asm volatile("fence.mbarrier_init.release.cluster;" ::: "memory");
        TSTAMP(11);
      }
      __syncwarp();
      asm volatile("bar.arrive 0, 512;" ::: "memory");
      if (elect()) {
        head_x(0);
#pragma unroll
        for (int b = 0; b < 6; b++)
          tma_load(sb + SM_H + 16384 + b * 4096, &P.wBh, (b >> 1) * DM + wcol, (b & 1) * 32, bar + 8 * B_FULLH);
        if (p < 3) tma_prefetch_l2(&P.xB, (4 + p) * 64, r * 128);
        tma_prefetch_l2(&P.wBh, (r % 3) * DM + wcol, 256 + (r / 3) * 32);
      }
      __syncwarp();
    } else {
      if (elect()) {
#pragma unroll
        for (int w = 1; w < 4; w++) {
          if (warp == w) {
#pragma unroll
            for (int i = 3 + w; i < B_COUNT; i += 3) {
              uint32_t c = 1;
              if ((i >= B_EMPTYH && i < B_EMPTYH + 3) || (i >= B_EMPTYKV && i < B_EMPTYKV + 4) || i == B_PUBA) c = 4;
              if (i == B_OWNRDY) c = 8;
              if (i == B_STOREDONE) c = 5;
              if (i == B_ATTNDONE || i == B_LOOPDONE || i == B_H3FREE) c = 2;
              mbar_init(bar + 8 * i, c);
            }
          }
        }
        asm volatile("fence.mbarrier_init.release.cluster;" ::: "memory");
      }
      __syncwarp();
      asm volatile("bar.sync 0, 512;" ::: "memory");
    }
    asm volatile("barrier.cluster.arrive.relaxed.aligned;" ::: "memory");
    asm volatile("ld.volatile.global.u32 %0, [%1];" : "=r"(tag) : "l"(P.epoch));
    if (warp == 0) {
      asm volatile("barrier.cluster.wait.acquire.aligned;" ::: "memory");
      if (elect()) {
#pragma unroll 1
        for (int c = 1; c < 7; c++) {
          if (c >= 4) mbar_wait(bar + 8 * (B_EMPTYH + c - 4), 0);
          head_x(c);
          const uint32_t st = sb + SM_H + (c & 3) * H_STAGE + 16384 + rank * 4096, fb = bar + 8 * (B_FULLH + (c & 3));
#pragma unroll
          for (int b = 0; b < 3; b++) tma_load_mc(st + b * 8192, &P.wBh, b * DM + wcol, c * 64 + rank * 32, fb);
          if (c == 3) { TSTAMP(12); prefetch_map(&P.kv); prefetch_map(&P.oB); prefetch_map(&P.outs); }
        }
      }
      __syncwarp();
      uint32_t ready = 0, todo = ~(15u << (4 * ci));
#pragma unroll 1
      for (int j = 2; j < 32; j++) {
        const int s = j & 3;
        uint32_t it = 0;
        const uint32_t want = j < 30 ? todo : 1u << (2 * (r ^ 1) + (j & 1));
        while (!(ready & want)) {
          ready = __ballot_sync(0xffffffffu, ld_flag(&P.flags[F_KV + p * 32 + lane]) == tag);
          if (++it > SPIN_LIMIT) trap_now();
        }
        const uint32_t m = ready & want, hi = m >> (2 * r) << (2 * r);
        const int blk = __ffs(hi ? hi : m) - 1;
        todo &= ~(1u << blk);
        __syncwarp();
        if (elect()) {
          if (it) fence_async_all();
          const uint32_t fb = bar + 8 * (B_FULLKV + s);
          mbar_wait(bar + 8 * (B_EMPTYKV + s), ((j - 2) >> 2) & 1);
          mbar_expect(fb, 16384);
          if (j < 30) {
            tma_load_mc(sb + SM_KV + s * 16384 + rank * 8192, &P.kv, 0, (2 * p + rank) * S_LEN + blk * 64, fb);
          } else {
            tma_load(sb + SM_KV + s * 16384, &P.kv, 0, (2 * p) * S_LEN + blk * 64, fb);
            tma_load(sb + SM_KV + s * 16384 + 8192, &P.kv, 0, (2 * p + 1) * S_LEN + blk * 64, fb);
          }
          if (j == 2) TSTAMP(9);
        }
        __syncwarp();
      }
      if (elect()) mbar_wait(bar + 8 * B_ATTNDONE, 0);
      __syncwarp();
      uint32_t left = 0xff, have = 0;
#pragma unroll 1
      for (int n = 0; n < 8; n++) {
        uint32_t it = 0;
        while (!(have & left)) {
          have = __ballot_sync(0xffffffffu, lane < 8 && ld_flag(&P.flags[F_OB + (G >> 1) * 8 + lane]) == tag);
          if (++it > SPIN_LIMIT) trap_now();
        }
        const int c = __ffs(have & left) - 1;
        left &= ~(1u << c);
        __syncwarp();
        if (elect()) {
          if (it) fence_async_all();
          asm volatile("st.shared.u32 [%0], %1;" ::"r"(sb + SM_ORDER + 4 * n), "r"(c < 7 ? c * 448 : 3072) : "memory");
          mbar_expect(bar + 8 * (B_FULLOB + n), 8192);
          tma_load(sb + SM_KV + n * 8192, &P.oB, c * 64, G * 64, bar + 8 * (B_FULLOB + n));
          if (n == 7) TSTAMP(10);
        }
        __syncwarp();
      }
    } else if (warp == 1) {
      if (A_ON && elect()) {
        prefetch_map(&P.xA);
        prefetch_map(&P.wA);
        mbar_wait(bar + 8 * (B_EMPTYH + 1), 0);
        if (tag == 0) trap_now();
        if (p < 7) tma_prefetch_l2(&P.xA, p * 64, r * 128);
#pragma unroll 1
        for (int b = 0; b < 3; b++) tma_prefetch_l2(&P.wA, (2 - b) * DM + wcol, (r % 7) * 64);
        prefetch_map(&P.woA);
        prefetch_map(&P.woB);
        prefetch_map(&P.oA);
        mbar_wait(bar + 8 * B_H3FREE, 0);
        mbar_wait(bar + 8 * (B_FULLH + 2), 1);
        int c = 6, col = 2 * DM + wcol;
#pragma unroll 1
        for (int n = 0; n < 21; n++) {
          const int s = n & 3;
          if (n < 7) {
            if (n == 1) mbar_wait(bar + 8 * (B_FULLKV + AWAIT), 0);
            if (n > AFLY) mbar_wait(bar + 8 * (B_FULLXA + n - 1 - AFLY), 0);
            mbar_expect(bar + 8 * (B_FULLXA + c), 16384);
            tma_load(sb + SM_XA + c * 16384, &P.xA, c * 64, r * 128, bar + 8 * (B_FULLXA + c));
          }
          if (n >= 4) mbar_wait(bar + 8 * (B_EMPTYWA + s), ((n >> 2) - 1) & 1);
          mbar_expect(bar + 8 * (B_FULLWA + s), 8192);
          tma_load(sb + SM_WA + s * 8192, &P.wA, col, c * 64, bar + 8 * (B_FULLWA + s));
          if (++c == 7) c = 0;
          if (c == 6) col -= DM;
        }
        mbar_wait(bar + 8 * B_XAFREE, 0);
#pragma unroll 1
        for (int n = 0; n < 7; n++) {
          const uint32_t fb = bar + 8 * (B_FULLXA + n);
          if (n >= 2) mbar_wait(fb - 16, 1);
          mbar_expect(fb, 16384);
          tma_load(sb + SM_XA + n * 8192, &P.woA, cg * 112, n * 64, fb);
          tma_load(sb + SM_XA + 57344 + n * 8192, &P.woA, cg * 112 + 64, n * 64, fb);
        }
      }
      __syncwarp();
      uint32_t left = A_ON ? 0xff : 0, have = 0;
#pragma unroll 1
      for (int n = 21; left; n++) {
        const int s = n & 3;
        uint32_t it = 0;
        while (!(have & left)) {
          have = __ballot_sync(0xffffffffu, lane < 8 && ld_flag(&P.flags[F_OA + (G >> 1) * 8 + lane]) == tag);
          if (++it > SPIN_LIMIT) trap_now();
          if (!(have & left)) __nanosleep(200);
        }
        const int c = __ffs(have & left) - 1;
        left &= ~(1u << c);
        __syncwarp();
        if (elect()) {
          if (it) fence_async_all();
          mbar_wait(bar + 8 * (B_EMPTYWA + s), ((n >> 2) - 1) & 1);
          asm volatile("st.shared.u32 [%0], %1;" ::"r"(sb + SM_ORDER + 32 + 4 * (n - 21)), "r"(c) : "memory");
          mbar_expect(bar + 8 * (B_FULLWA + s), 8192);
          tma_load(sb + SM_WA + s * 8192, &P.oA, c * 64, G * 64, bar + 8 * (B_FULLWA + s));
        }
        __syncwarp();
      }
    } else if (warp == 2) {
      if (elect()) {
        mbar_wait(bar + 8 * B_OWNRDY, 0);
        TSTAMP(15);
#pragma unroll 1
        for (int h = 0; h < 2; h++) {
          tma_store(&P.kv, 0, (2 * p) * S_LEN + r * 128 + h * 64, sb + SM_KV + h * 16384);
          tma_store(&P.kv, 0, (2 * p + 1) * S_LEN + r * 128 + h * 64, sb + SM_KV + h * 16384 + 8192);
          bulk_commit();
          bulk_wait();
          mbar_arrive(bar + 8 * (B_STOREDONE + h));
          st_release(&P.flags[F_KV + p * 32 + 2 * r + h], tag);
          if (h == 0) TSTAMP(14); else TSTAMP(8);
        }
        if (A_ON) {
          mbar_wait(bar + 8 * B_PUBA, 0);
          tma_store(&P.oA, 64 * p, r * 128, sb + SM_STG);
          tma_store(&P.oA, 64 * p, r * 128 + 64, sb + SM_STG + 8192);
          bulk_commit();
          bulk_wait();
        }
        mbar_arrive(bar + 8 * B_STGFREE);
        if (A_ON) st_release(&P.flags[F_OA + r * 8 + p], tag);
        TSTAMP(20);
        mbar_wait(bar + 8 * B_ATTNDONE, 0);
        tma_store(&P.oB, 64 * p, r * 128, sb + SM_STG);
        tma_store(&P.oB, 64 * p, r * 128 + 64, sb + SM_STG + 8192);
        bulk_commit();
        bulk_wait();
        TSTAMP(13);
        mbar_arrive(bar + 8 * B_STGFREE);
        st_release(&P.flags[F_OB + r * 8 + p], tag);
        TSTAMP(5);
      }
      __syncwarp();
    } else {
      uint32_t kn = 0, vm = 0, it = 0;
#pragma unroll 1
      for (int u = 0; u < 2; u++) {
        const unsigned long long* src = P.stats + (size_t)(p * 64 + lane * 2 + u) * 2;
        unsigned long long a, b;
        while (true) {
          asm volatile("ld.relaxed.gpu.global.u64 %0, [%1];" : "=l"(a) : "l"(src) : "memory");
          asm volatile("ld.relaxed.gpu.global.u64 %0, [%1];" : "=l"(b) : "l"(src + 1) : "memory");
          if ((unsigned)(a >> 32) == tag && (unsigned)(b >> 32) == tag) break;
          if (++it > SPIN_LIMIT) trap_now();
          __nanosleep(500);
        }
        kn = __vmaxu2(kn, (uint32_t)a);
        vm = __vmaxu2(vm, (uint32_t)b);
      }
#pragma unroll 1
      for (int o = 16; o; o >>= 1) {
        kn = __vmaxu2(kn, __shfl_xor_sync(0xffffffffu, kn, o));
        vm = __vmaxu2(vm, __shfl_xor_sync(0xffffffffu, vm, o));
      }
      if (elect()) {
        asm volatile("st.shared.v2.u32 [%0], {%1, %2};" ::"r"(sb + SM_STAT), "r"(kn), "r"(vm) : "memory");
        mbar_arrive(bar + 8 * B_STATS);
        mbar_expect(bar + 8 * B_FULLWOB, 7 * 16384);
#pragma unroll 1
        for (int c = 0; c < 7; c++) {
          mbar_wait(bar + 8 * (B_EMPTYXA + c), 0);
          tma_load(sb + SM_XA + c * 8192, &P.woB, cg * 112, c * 64, bar + 8 * B_FULLWOB);
          tma_load(sb + SM_XA + 57344 + c * 8192, &P.woB, cg * 112 + 48, c * 64, bar + 8 * B_FULLWOB);
        }
      }
      __syncwarp();
    }
  } else if (wg < 2) {
    asm volatile("bar.sync 0, 512;" ::: "memory");
    asm volatile("barrier.cluster.arrive.relaxed.aligned;" ::: "memory");
    asm volatile("ld.volatile.global.u32 %0, [%1];" : "=r"(tag) : "l"(P.epoch));
    asm volatile("setmaxnreg.inc.sync.aligned.u32 160;");
    const int t = threadIdx.x & 127, g = lane >> 2, c4 = lane & 3;
    uint32_t qA[8], qB[8];
    const uint32_t empty_l = bar + 8 * B_EMPTYKV, empty_r = mapa(empty_l, rank ^ 1);
    asm volatile("barrier.cluster.wait.acquire.aligned;" ::: "memory");
    {
      float acc[96];
      const uint32_t xd = desc_lo(sb + SM_H + wg * 8192, 16), wd = desc_lo(sb + SM_H + 16384, 8192) + (p & 1);
#pragma unroll 1
      for (int c = 0; c < 7; c++) {
        const uint32_t so = (c & 3) * (H_STAGE >> 4);
        mbar_wait(bar + 8 * (B_FULLH + (c & 3)), c >> 2);
        if (threadIdx.x == 0) TSTAMP(c ? 21 + c : 1);
        wg_fence();
#pragma unroll
        for (int kk = 0; kk < 4; kk++) mma_n192_ss_tb(acc, desc(xd + so + kk * 2), desc(wd + so + kk * 128), kk ? 1 : c);
        wg_commit();
        wg_wait<1>();
        if (c == 1 && tag == 0) trap_now();
        const bool rel = c > 0 && c < 4;
        mbar_arrive_if(bar + 8 * (B_EMPTYH - 1) + 8 * c, t == 0 && rel);
        mbar_arrive_cluster_if(empty_r - 8 * (B_EMPTYKV - B_EMPTYH + 1) + 8 * c, t == 32 && rel);
        mbar_arrive_if(bar + 8 * B_H3FREE, t == 64 && c == 4);
      }
      wg_wait<0>();
      pin(acc);
      if (threadIdx.x == 0) TSTAMP(2);
      mbar_arrive_if(empty_l + 16, t == 0);
      mbar_arrive_if(empty_l + 24, t == 0);
      mbar_arrive_cluster_if(empty_r + 16, t == 32);
      mbar_arrive_cluster_if(empty_r + 24, t == 32);
      const bool lo = c4 < 2;
      const int mrow = (lane & 7) + ((lane >> 3) & 1) * 8 + warp * 16;
      const uint32_t tile = sb + SM_KV + wg * 16384 + mrow * 128;
#pragma unroll
      for (int h = 0; h < 2; h++) {
#pragma unroll
        for (int ch = 0; ch < 8; ch += 2) {
          uint32_t v[4];
#pragma unroll
          for (int i = 0; i < 4; i++) {
            const int cc = ch + (i >> 1);
            const int b = (cc & 3) + 3 * h;
            const int a = 32 + (cc >> 2) * 32 + 4 * b + 2 * (i & 1);
            v[i] = pack_h(acc[a], acc[a + 1]);
            if (b == 3) {
              const uint32_t fill = (cc >= 4 && c4 == (h ? 0 : 2)) ? 0x00003c00u : 0u;
              v[i] = (lo == (h == 0)) ? v[i] : fill;
            }
          }
          stsm4(tile + h * 8192 + (((ch + (lane >> 4)) ^ (mrow & 7)) << 4), v[0], v[1], v[2], v[3]);
        }
      }
      fence_async_smem();
      __syncwarp();
      mbar_arrive_if(bar + 8 * B_OWNRDY, lane == 0);
#pragma unroll
      for (int i = 0; i < 8; i++) {
        const int a = 4 * (i >> 1) + 2 * (i & 1);
        qA[i] = pack_h(acc[a] * QSCALE, acc[a + 1] * QSCALE);
        qB[i] = pack_h(acc[12 + a] * QSCALE, acc[13 + a] * QSCALE);
      }
      if (!lo) qA[6] = qA[7] = 0;
      if (lo) qB[0] = qB[1] = 0;
    }
    float qn[2];
#pragma unroll
    for (int h = 0; h < 2; h++) {
      const uint32_t (&q)[8] = h ? qB : qA;
      uint32_t n0 = 0, n1 = 0;
#pragma unroll
      for (int i = 0; i < 4; i++) { n0 = hfma2(q[2 * i], q[2 * i], n0); n1 = hfma2(q[2 * i + 1], q[2 * i + 1], n1); }
      float a = h_lo(n0) + h_hi(n0), b = h_lo(n1) + h_hi(n1);
      a += __shfl_xor_sync(0xffffffffu, a, 1);
      b += __shfl_xor_sync(0xffffffffu, b, 1);
      a += __shfl_xor_sync(0xffffffffu, a, 2);
      b += __shfl_xor_sync(0xffffffffu, b, 2);
      qn[h] = __uint_as_float(max(__float_as_uint(a), __float_as_uint(b)));
    }
    mbar_wait(bar + 8 * B_OWNRDY, 0);
    if (threadIdx.x == 0) TSTAMP(3);

    float oA[16], oB[16];
    uint32_t sA[16], sB[16], pA[16], pB[16];
    uint32_t k0 = desc_lo(sb + SM_KV, 16), v0;
    const uint32_t zero = P.zero;
    uint32_t chain = 0x3c003c00u;
    auto pv_qk = [&](float (&o)[16], const uint32_t (&pp)[16], uint32_t vd, uint32_t (&s)[16], const uint32_t (&q)[8], uint32_t kd) {
      mma_pv(o, pp[0], pp[1], pp[2], pp[3], desc(vd), 1);
      mma_qk(s, q[0], q[1], q[2], q[3], desc(kd), 0);
      mma_pv(o, pp[4], pp[5], pp[6], pp[7], desc(vd + 128), 1);
      mma_qk(s, q[4], q[5], q[6], q[7], desc(kd + 2), 1);
      mma_pv(o, pp[8], pp[9], pp[10], pp[11], desc(vd + 256), 1);
      mma_pv(o, pp[12], pp[13], pp[14], pp[15], desc(vd + 384), 1);
    };
#pragma unroll
    for (int i = 0; i < 16; i++) { oA[i] = oB[i] = 0.f; pB[i] = 0; }
    pin(qA); pin(qB); pin(oA); pin(oB);
    wg_fence();
    mma_qk(sA, qA[0], qA[1], qA[2], qA[3], desc(k0), 0);
    mma_qk(sA, qA[4], qA[5], qA[6], qA[7], desc(k0 + 2), 1);
    wg_commit();
    wg_wait<0>();
    pin(sA);
#pragma unroll 1
    for (int o = 0; o < 8; o++) {
      k0 = __shfl_sync(0xffffffffu, k0, 0);
      v0 = k0 + 4;
#pragma unroll
      for (int u = 0; u < 4; u++) {
        const uint32_t so = u * 1024, sp = ((u + 3) & 3) * 1024, sn = ((u + 1) & 3) * 1024;
        const uint32_t fbar = bar + 8 * (B_FULLKV + ((u + 1) & 3)), par = (u == 0 ? o + 1 : o) & 1;
        const bool nowait = (u == 0 && o == 0) || (u == 3 && o == 7);
        const uint32_t have = mbar_test(fbar, par) | nowait;
        pin(pB);
        wg_fence();
        pv_qk(oB, pB, v0 + 512 + (u == 0 && o == 0 ? 0 : sp), sB, qB, k0 + so + 512);
        wg_commit();
        exp_tile(sA, pA, zero, chain);
        pin(pA);
        wg_wait<0>();
        pin(sB); pin(oB); pin(sA);
        if (u == 1 || u == 2) mbar_wait(bar + 8 * (B_STOREDONE + u - 1), 0, o);
        mbar_wait(fbar, par, have);
        const bool rel = u == 0 ? o > 0 : (o < 7);
        mbar_arrive_if(empty_l + (sp >> 7), t == 0 && rel);
        mbar_arrive_cluster_if(empty_r + (sp >> 7), t == 32 && rel);
        wg_fence();
        pv_qk(oA, pA, v0 + so, sA, qA, k0 + sn);
        wg_commit();
        exp_tile(sB, pB, zero, chain);
        pin(pB);
        wg_wait<0>();
        pin(sA); pin(oA); pin(sB);
      }
    }
    wg_fence();
#pragma unroll
    for (int kk = 0; kk < 4; kk++) mma_pv(oB, pB[4 * kk], pB[4 * kk + 1], pB[4 * kk + 2], pB[4 * kk + 3], desc(v0 + 3 * 1024 + 512 + kk * 128), 1);
    wg_commit();
    if (threadIdx.x == 0) TSTAMP(29);
    mbar_wait(bar + 8 * B_STATS, 0);
    mbar_wait(bar + 8 * B_STGFREE, 0);
    uint32_t kn, vm;
    asm volatile("ld.shared.v2.u32 {%0, %1}, [%2];" : "=r"(kn), "=r"(vm) : "r"(sb + SM_STAT));
    bool ok = qn[0] * h_lo(kn) <= 1024.f && qn[1] * h_hi(kn) <= 1024.f && qn[0] <= 65504.f && qn[1] <= 65504.f &&
              h_lo(kn) <= 65504.f && h_hi(kn) <= 65504.f && h_lo(vm) <= 65504.f && h_hi(vm) <= 65504.f &&
              h_lo(vm) >= 0x1p-10f && h_hi(vm) >= 0x1p-10f && !P.force_slow;
    wg_wait<0>();
    pin(oB);
    if (threadIdx.x == 0) TSTAMP(4);
    mbar_arrive_if(bar + 8 * B_LOOPDONE, t == 0);
    {
      uint32_t v[14];
#pragma unroll
      for (int hr = 0; hr < 2; hr++) {
        const float lA = __shfl_sync(0xffffffffu, oA[12 + 2 * hr], (lane & ~3) | 2);
        const float lB = __shfl_sync(0xffffffffu, oB[2 * hr], lane & ~3);
        ok = ok && lA >= 128.f && lA < 16384.f && lB >= 128.f && lB < 16384.f;
        const float iA = rcp_f(lA), iB = rcp_f(lB);
#pragma unroll
        for (int b = 0; b < 7; b++) {
          float a0, a1;
          if (b < 3) { a0 = oA[4 * b + 2 * hr] * iA; a1 = oA[4 * b + 2 * hr + 1] * iA; }
          else if (b > 3) { a0 = oB[4 * (b - 3) + 2 * hr] * iB; a1 = oB[4 * (b - 3) + 2 * hr + 1] * iB; }
          else if (c4 < 2) { a0 = oA[12 + 2 * hr] * iA; a1 = oA[13 + 2 * hr] * iA; }
          else { a0 = oB[2 * hr] * iB; a1 = oB[2 * hr + 1] * iB; }
          v[2 * b + hr] = pack_b(a0, a1);
        }
      }
      stage64(sb + SM_STG + wg * 8192 + warp * 2048, v, lane, p == 7);
      fence_async_smem();
    }
    if (__builtin_expect(named_or(2 + wg, 128, !ok), 0)) {
      mbar_wait(bar + 8 * B_LOOPDONE, 0);
      uint8_t* base = smem_raw + (sb - (uint32_t)__cvta_generic_to_shared(smem_raw));
      slow_attention(P.xBp, P.wBp, reinterpret_cast<float*>(base + SM_KV + wg * 32768),
                     reinterpret_cast<uint32_t*>(base + SM_STG + wg * 8192), r * 128 + wg * 64, p, t, 2 + wg);
      fence_async_smem();
      named_sync(2 + wg, 128);
    }
    if (threadIdx.x == 0) TSTAMP(28);
    mbar_arrive_if(bar + 8 * B_ATTNDONE, t == 0);
    {
      float o[28];
      const uint32_t od = desc_lo(sb + SM_KV, 16), wo = desc_lo(sb + SM_XA + wg * (57344 + 16), 16);
      mbar_wait(bar + 8 * B_FULLWOB, 0);
#pragma unroll 1
      for (int n = 0; n < 8; n++) {
        mbar_wait(bar + 8 * (B_FULLOB + n), 0);
        uint32_t c;
        asm volatile("ld.shared.u32 %0, [%1];" : "=r"(c) : "r"(sb + SM_ORDER + 4 * n) : "memory");
        const uint32_t wc = wo + __shfl_sync(0xffffffffu, c, 0);
        if (n == 0 && threadIdx.x == 0) TSTAMP(6);
        wg_fence();
#pragma unroll
        for (int kk = 0; kk < 4; kk++) mma_n56_ss_tb(o, desc(od + n * 512 + kk * 2), desc(wc + kk * 128), kk ? 1 : n);
        wg_commit();
      }
      wg_wait<0>();
      pin(o);
      uint32_t v[14];
#pragma unroll
      for (int i = 0; i < 14; i++) v[i] = pack_b(o[2 * i], o[2 * i + 1]);
      mbar_wait(bar + 8 * B_STGFREE, 1);
      stage56(sb + SM_STG + wg * 8192 + warp * (16 * 112), v, lane);
      fence_async_smem();
      named_sync(2 + wg, 128);
      if (t == 0) {
        tma_store(&P.outs, DM + cg * 112 + wg * 56, G * 64, sb + SM_STG + wg * 8192);
        bulk_commit();
        asm volatile("cp.async.bulk.wait_group 0;" ::: "memory");
      }
    }
    if (threadIdx.x == 0) { TSTAMP(7); GSTAMP(31); }
    if (blockIdx.x == 0 && threadIdx.x == 0) *(volatile unsigned*)P.epoch = tag + 1 ? tag + 1 : 1;
    if (threadIdx.x == 0) TDUMP();
  } else {
    asm volatile("bar.sync 0, 512;" ::: "memory");
    asm volatile("barrier.cluster.arrive.relaxed.aligned;" ::: "memory");
    asm volatile("ld.volatile.global.u32 %0, [%1];" : "=r"(tag) : "l"(P.epoch));
    asm volatile("setmaxnreg.inc.sync.aligned.u32 152;");
    const int t = threadIdx.x & 127, g = lane >> 2, c4 = lane & 3;
    auto kv_stats = [&]() {
    mbar_wait(bar + 8 * B_OWNRDY, 0);
    {
      uint32_t sk = 0, sv = 0;
#pragma unroll 1
      for (int h = 0; h < 2; h++) {
        const uint32_t rowa = sb + SM_KV + (t >> 6) * 16384 + h * 8192 + (t & 63) * 128;
        uint32_t n2 = 0, vm = 0;
#pragma unroll
        for (int ch = 0; ch < 8; ch++) {
          uint32_t v[4];
          asm volatile("ld.shared.v4.u32 {%0, %1, %2, %3}, [%4];" : "=r"(v[0]), "=r"(v[1]), "=r"(v[2]), "=r"(v[3])
                       : "r"(rowa + ((ch ^ (t & 7)) << 4)));
          if (ch == 7 && h == 0) v[2] = 0;
          if (ch == 4 && h == 1) v[0] = 0;
#pragma unroll
          for (int i = 0; i < 4; i++) {
            if (ch < 4) n2 = hfma2(v[i], v[i], n2);
            else vm = habsmax2(vm, v[i]);
          }
        }
        const uint32_t ns = __half_as_ushort(__float2half_rn(h_lo(n2) + h_hi(n2)));
        sk |= __reduce_max_sync(0xffffffffu, ns) << (16 * h);
        sv |= __reduce_max_sync(0xffffffffu, max(vm & 0xffffu, vm >> 16)) << (16 * h);
      }
      if (lane == 0) {
        mbar_arrive(bar + 8 * B_STOREDONE);
        unsigned long long* dst = P.stats + (size_t)(p * 64 + r * 4 + warp) * 2;
        const unsigned long long hi = (unsigned long long)tag << 32;
        asm volatile("st.relaxed.gpu.global.u64 [%0], %1;" ::"l"(dst), "l"(hi | sk) : "memory");
        asm volatile("st.relaxed.gpu.global.u64 [%0], %1;" ::"l"(dst + 1), "l"(hi | sv) : "memory");
      }
    }
      if (t == 0) TSTAMP(16);
    };
    if (!A_ON) {
      kv_stats();
      mbar_wait(bar + 8 * (B_FULLKV + 3), 0);
      if (t == 0) for (int c = 0; c < 7; c++) mbar_arrive(bar + 8 * (B_EMPTYXA + c));
    } else {
    const uint32_t xa = desc_lo(sb + SM_XA, 16), oa = desc_lo(sb + SM_WA, 16), wa = oa + (p & 1);
    {
      float acc[64];
#pragma unroll 1
      for (int n = 0; n < 14; n++) {
        const int c = (n == 0 || n == 7) ? 6 : (n < 7 ? n - 1 : n - 8);
        if (t == 0) ISTAMP(8 + n, clock());
        mbar_wait(bar + 8 * (B_FULLXA + c), 0, n >= 7);
        mbar_wait(bar + 8 * (B_FULLWA + (n & 3)), (n >> 2) & 1);
        if (t == 0) ISTAMP(72 + n, clock());
#pragma unroll
        for (int kk = 0; kk < 4; kk++) {
          if (kk % AGRP == 0) wg_fence();
          mma_n128_ss_ta(acc, desc(wa + (n & 3) * 512 + kk * 128), desc(xa + c * 1024 + kk * 2), kk ? 1 : c != 6);
          if (kk % AGRP == AGRP - 1) { wg_commit(); wg_wait<0>(); }
        }
        mbar_arrive_if(bar + 8 * (B_EMPTYWA + (n & 3)), t == 0);
        if (n == 0) kv_stats();
        if (n == 6) {
          pin(acc);
          const int mrow = (lane & 7) + ((lane >> 3) & 1) * 8 + warp * 16;
          const uint32_t one = g == 0 ? 0x3f803f80u : 0u;
#pragma unroll
          for (int b = 0; b < 16; b += 2) {
            const int ch = (b & 7) + (lane >> 4);
            const uint32_t hi0 = pack_b(acc[4 * b + 2], acc[4 * b + 3]), hi1 = pack_b(acc[4 * b + 6], acc[4 * b + 7]);
            stsm4(sb + SM_STG + (b >> 3) * 8192 + mrow * 128 + ((ch ^ (mrow & 7)) << 4), pack_b(acc[4 * b], acc[4 * b + 1]),
                  warp == 3 ? one : hi0, pack_b(acc[4 * b + 4], acc[4 * b + 5]), warp == 3 ? one : hi1);
          }
          fence_async_smem();
          named_sync(1, 128);
        }
      }
      pin(acc);
      uint32_t pk[32];
#pragma unroll
      for (int i = 0; i < 32; i++) pk[i] = phi2(acc[2 * i], acc[2 * i + 1]);
      float kv[32];
      const uint32_t vt = desc_lo(sb + SM_STG, 16);
      pin(pk);
      if (t == 0) ISTAMP(96 + 15, clock());
#pragma unroll
      for (int kk = 0; kk < 8; kk++) {
        if (!(kk & 3)) wg_fence();
        mma_n64_rs(kv, pk[4 * kk], pk[4 * kk + 1], pk[4 * kk + 2], pk[4 * kk + 3], desc(vt + (kk >> 2) * 512 + (kk & 3) * 2), kk);
        if ((kk & 3) == 3) { wg_commit(); wg_wait<0>(); }
      }
      pin(kv);
      if (t == 0) ISTAMP(96 + 22, clock());
#pragma unroll
      for (int hr = 0; hr < 2; hr++) {
        const int dk = warp * 16 + hr * 8 + g;
        uint4* dst = P.part + (size_t)((p * 16 + r) * 56 + dk) * 32 + c4;
#pragma unroll
        for (int b = 0; b < 8; b++) {
          const int cp = 4 * b + c4;
          if (dk < 56 && (cp == 28 || (cp < 28 && (cp >= 14) == (dk >= DH))))
            asm volatile("st.relaxed.gpu.global.v4.u32 [%0], {%1, %2, %3, %3};" ::"l"(dst + 4 * b),
                         "r"(__float_as_uint(kv[4 * b + 2 * hr])), "r"(__float_as_uint(kv[4 * b + 2 * hr + 1])), "r"(tag) : "memory");
        }
      }
    }
    if (t == 0) TSTAMP(17);
    float q[2][32];
    const int dk = r * 4 + warp;
    const bool red_on = dk < 56 && (lane == 28 || (lane < 28 && (lane >= 14) == (dk >= DH)));
    const uint4* red_src = P.part + (size_t)(p * 16 * 56 + dk) * 32 + lane;
    uint4 v[8];
    float ra = 0.f, rb = 0.f;
    auto load8 = [&](const uint4* src, int stride) {
#pragma unroll
      for (int i = 0; i < 8; i++)
        asm volatile("ld.relaxed.gpu.global.v4.u32 {%0, %1, %2, %3}, [%4];" : "=r"(v[i].x), "=r"(v[i].y), "=r"(v[i].z), "=r"(v[i].w)
                     : "l"(src + (size_t)i * stride) : "memory");
    };
#pragma unroll 1
    for (int i = 0; i < 7; i++) {
      const int n = 14 + i, c = i ? i - 1 : 6;
      if (t == 0) ISTAMP(8 + n, clock());
      mbar_wait(bar + 8 * (B_FULLWA + (n & 3)), (n >> 2) & 1);
      if (t == 0) ISTAMP(72 + n, clock());
      if ((i == 3 || i == 4) && red_on) load8(red_src, 56 * 32);
#pragma unroll
      for (int kk = 0; kk < 4; kk++) {
        const uint64_t bd = desc(wa + (n & 3) * 512 + kk * 128);
        if (kk % AGRP == 0) wg_fence();
        mma_n64_ss_tb(q[0], desc(xa + c * 1024 + kk * 2), bd, kk ? 1 : i);
        mma_n64_ss_tb(q[1], desc(xa + c * 1024 + 512 + kk * 2), bd, kk ? 1 : i);
        if (kk % AGRP == AGRP - 1) { wg_commit(); wg_wait<0>(); }
      }
      mbar_arrive_if(bar + 8 * (B_EMPTYWA + (n & 3)), t == 0);
      if (i == 3 || i == 4) {
        if (red_on) {
          uint32_t it = 0;
          while (true) {
            bool ok = true;
#pragma unroll
            for (int k = 0; k < 8; k++) ok = ok && v[k].z == tag;
            if (ok) break;
            if (++it > SPIN_LIMIT) trap_now();
            __nanosleep(300);
            load8(red_src, 56 * 32);
          }
#pragma unroll
          for (int k = 0; k < 8; k++) { ra += __uint_as_float(v[k].x); rb += __uint_as_float(v[k].y); }
          red_src += 8 * 56 * 32;
        }
        __syncwarp();
        if (i == 4) {
          if (lane == 28) { if (dk >= DH) { rb = ra; ra = 0.f; } else rb = 0.f; }
          asm volatile("st.relaxed.gpu.global.v2.u32 [%0], {%1, %2};" ::"l"(P.kvf + (size_t)(p * 64 + dk) * 32 + lane),
                       "r"(pack_b(ra, rb)), "r"(tag) : "memory");
          if (t == 0) TSTAMP(21);
        }
      }
    }
    pin(q[0]);
    pin(q[1]);
    mbar_arrive_if(bar + 8 * B_XAFREE, t == 0);
    if (t == 0) ISTAMP(96 + 16, clock());
    uint32_t pq[2][16];
#pragma unroll
    for (int i = 0; i < 14; i++) pq[0][i] = phi2(q[0][2 * i], q[0][2 * i + 1]);
    const uint4* gsrc = reinterpret_cast<const uint4*>(P.kvf + (size_t)(p * 64 + warp * 16) * 32) + lane;
    if (t == 0) ISTAMP(96 + 17, clock());
    load8(gsrc, 32);
#pragma unroll
    for (int i = 0; i < 14; i++) pq[1][i] = phi2(q[1][2 * i], q[1][2 * i + 1]);
    pq[0][14] = pq[0][15] = pq[1][14] = pq[1][15] = 0;
    pin(pq[1]);
    if (t == 0) ISTAMP(96 + 18, clock());
    {
      uint32_t it = 0;
      while (true) {
        bool ok = true;
#pragma unroll
        for (int i = 0; i < 8; i++) ok = ok && v[i].y == tag && v[i].w == tag;
        if (ok) break;
        if (++it > SPIN_LIMIT) trap_now();
        __nanosleep(300);
        load8(gsrc, 32);
      }
      __syncwarp();
      if (t == 0) { ISTAMP(96 + 19, clock()); ISTAMP(96 + 23, it); }
#pragma unroll
      for (int i = 0; i < 8; i++) {
        const int row = warp * 16 + 2 * i + (lane >> 4);
        asm volatile("st.shared.v2.u32 [%0], {%1, %2};" ::"r"(sb + SM_STG + row * 128 + ((((lane & 15) >> 1) ^ (row & 7)) << 4) + (lane & 1) * 8),
                     "r"(v[i].x), "r"(v[i].z) : "memory");
      }
      fence_async_smem();
      named_sync(1, 128);
    }
    if (t == 0) ISTAMP(96 + 20, clock());
    {
      const uint32_t kd = desc_lo(sb + SM_STG, 16);
      pin(pq[0]);
      pin(pq[1]);
#pragma unroll
      for (int kk = 0; kk < 4; kk++) {
        if (!(kk & 1)) wg_fence();
        mma_n64_rs_tb(q[0], pq[0][4 * kk], pq[0][4 * kk + 1], pq[0][4 * kk + 2], pq[0][4 * kk + 3], desc(kd + kk * 128), kk);
        mma_n64_rs_tb(q[1], pq[1][4 * kk], pq[1][4 * kk + 1], pq[1][4 * kk + 2], pq[1][4 * kk + 3], desc(kd + kk * 128), kk);
        if (kk & 1) { wg_commit(); wg_wait<0>(); }
      }
      pin(q[0]);
      pin(q[1]);
      if (t == 0) ISTAMP(96 + 21, clock());
#pragma unroll
      for (int m = 0; m < 2; m++) {
        uint32_t v[14];
#pragma unroll
        for (int hr = 0; hr < 2; hr++) {
          const float i0 = rcp_f(__shfl_sync(0xffffffffu, q[m][28 + 2 * hr], lane & ~3) + 1e-6f);
          const float i1 = rcp_f(__shfl_sync(0xffffffffu, q[m][29 + 2 * hr], lane & ~3) + 1e-6f);
#pragma unroll
          for (int b = 0; b < 7; b++) {
            const float inv = b < 3 ? i0 : (b > 3 ? i1 : (c4 < 2 ? i0 : i1));
            v[2 * b + hr] = pack_b(q[m][4 * b + 2 * hr] * inv, q[m][4 * b + 2 * hr + 1] * inv);
          }
        }
        stage64(sb + SM_STG + m * 8192 + warp * 2048, v, lane, p == 7);
      }
      fence_async_smem();
      __syncwarp();
      mbar_arrive_if(bar + 8 * B_PUBA, lane == 0);
    }
    if (t == 0) TSTAMP(18);
    {
      float o[56];
      const uint32_t wo = desc_lo(sb + SM_XA, 57344);
#pragma unroll 1
      for (int i = 0; i < 7; i++) mbar_wait(bar + 8 * (B_FULLXA + i), 1);
      uint32_t done = 0;
#pragma unroll 1
      for (int i = 0; i < 8; i++) {
        const int n = 21 + i;
        if (t == 0 && i < 7) ISTAMP(56 + i, clock());
        mbar_wait(bar + 8 * (B_FULLWA + (n & 3)), (n >> 2) & 1);
        if (t == 0 && i < 7) ISTAMP(120 + i, clock());
        uint32_t c;
        asm volatile("ld.shared.u32 %0, [%1];" : "=r"(c) : "r"(sb + SM_ORDER + 32 + 4 * i) : "memory");
        c = __shfl_sync(0xffffffffu, c, 0);
        const uint32_t wc = wo + (c < 7 ? c * 448 : 3072);
#pragma unroll
        for (int kk = 0; kk < 4; kk++) {
          if (kk % AGRP == 0) wg_fence();
          mma_n112_ss_tb(o, desc(oa + (n & 3) * 512 + kk * 2), desc(wc + kk * 128), kk ? 1 : i);
          if (kk % AGRP == AGRP - 1) { wg_commit(); wg_wait<0>(); }
        }
        mbar_arrive_if(bar + 8 * (B_EMPTYWA + (n & 3)), t == 0);
        done |= 1u << c;
        mbar_arrive_if(bar + 8 * (B_EMPTYXA - 1) + 8 * c, t == 0 && ((done << 1) >> c & 1));
        mbar_arrive_if(bar + 8 * B_EMPTYXA + 8 * c, t == 32 && (done >> (c + 1) & 1));
      }
      pin(o);
#pragma unroll
      for (int m = 0; m < 2; m++) {
        uint32_t v[14];
#pragma unroll
        for (int i = 0; i < 14; i++) v[i] = pack_b(o[28 * m + 2 * i], o[28 * m + 2 * i + 1]);
        stage56(sb + SM_WA + m * 7168 + warp * (16 * 112), v, lane);
      }
      fence_async_smem();
      named_sync(1, 128);
      if (t == 0) {
        tma_store(&P.outs, cg * 112, G * 64, sb + SM_WA);
        tma_store(&P.outs, cg * 112 + 56, G * 64, sb + SM_WA + 7168);
        bulk_commit();
        asm volatile("cp.async.bulk.wait_group 0;" ::: "memory");
      }
    }
    if (t == 0) TSTAMP(19);
    }
  }
}

typedef CUresult (*EncodeFn)(CUtensorMap*, CUtensorMapDataType, cuuint32_t, void*, const cuuint64_t*, const cuuint64_t*,
                             const cuuint32_t*, const cuuint32_t*, CUtensorMapInterleave, CUtensorMapSwizzle,
                             CUtensorMapL2promotion, CUtensorMapFloatOOBfill);

void make_map(EncodeFn enc, CUtensorMap* m, const void* ptr, uint64_t rows, uint64_t cols, uint32_t box_rows,
              uint32_t box_cols = 64) {
  cuuint64_t dims[2] = {cols, rows};
  cuuint64_t strides[1] = {cols * 2};
  cuuint32_t box[2] = {box_cols, box_rows};
  cuuint32_t es[2] = {1, 1};
  enc(m, CU_TENSOR_MAP_DATA_TYPE_BFLOAT16, 2, const_cast<void*>(ptr), dims, strides, box, es,
      CU_TENSOR_MAP_INTERLEAVE_NONE, box_cols == 64 ? CU_TENSOR_MAP_SWIZZLE_128B : CU_TENSOR_MAP_SWIZZLE_NONE,
      CU_TENSOR_MAP_L2_PROMOTION_L2_128B,
      CU_TENSOR_MAP_FLOAT_OOB_FILL_NONE);
}

}

#define DEV_FORCE_SLOW 0

extern "C" void kernel_launch(void* const* d_in, const int* in_sizes, int n_in, void* d_out, int out_size) {
  static EncodeFn enc = nullptr;
  static void *kv, *oA, *oB, *kvf, *part, *stats, *flags, *epoch;
  if (!enc) {
    void* fn = nullptr;
    cudaDriverEntryPointQueryResult q;
    cudaGetDriverEntryPoint("cuTensorMapEncodeTiled", &fn, cudaEnableDefault, &q);
    enc = (EncodeFn)fn;
    cudaGetSymbolAddress(&kv, g_kv);
    cudaGetSymbolAddress(&oA, g_oA);
    cudaGetSymbolAddress(&oB, g_oB);
    cudaGetSymbolAddress(&kvf, g_kvf);
    cudaGetSymbolAddress(&part, g_part);
    cudaGetSymbolAddress(&stats, g_stats);
    cudaGetSymbolAddress(&flags, g_flags);
    cudaGetSymbolAddress(&epoch, g_epoch);
    cudaFuncSetAttribute(fused_kernel, cudaFuncAttributeMaxDynamicSharedMemorySize, SMEM_BYTES);
  }
  Params P;
  make_map(enc, &P.xA, d_in[0], S_LEN, DM, 128);
  make_map(enc, &P.wA, d_in[1], DM, 3 * DM, 64);
  make_map(enc, &P.woA, d_in[2], DM, DM, 64);
  make_map(enc, &P.xB, d_in[3], S_LEN, DM, 128);
  make_map(enc, &P.wBh, d_in[4], DM, 3 * DM, 32);
  make_map(enc, &P.woB, d_in[5], DM, DM, 64);
  make_map(enc, &P.kv, kv, 16 * S_LEN, 64, 64);
  make_map(enc, &P.oA, oA, S_LEN, 512, 64);
  make_map(enc, &P.oB, oB, S_LEN, 512, 64);
  make_map(enc, &P.outs, d_out, S_LEN, 2 * DM, 64, 56);
  P.xBp = (const __nv_bfloat16*)d_in[3];
  P.wBp = (const __nv_bfloat16*)d_in[4];
  P.part = (uint4*)part;
  P.kvf = (uint2*)kvf;
  P.stats = (unsigned long long*)stats;
  P.flags = (unsigned*)flags;
  P.epoch = (unsigned*)epoch;
  P.force_slow = DEV_FORCE_SLOW;
  P.zero = 0;
  fused_kernel<<<128, 512, SMEM_BYTES>>>(P);
}
```

```cpp
#include <cuda_runtime.h>
#include <cuda_bf16.h>
#include <cuda_fp16.h>
#include <cuda.h>
#include <stdint.h>

namespace {

constexpr int S_LEN = 2048, DM = 448, DH = 28;
constexpr float QSCALE = 0.18898223650461362f * 1.4426950408889634f;

constexpr uint32_t SM_KV = 0;
constexpr uint32_t SM_H = 32768;
constexpr uint32_t H_STAGE = 40960;
constexpr uint32_t SM_XA = 65536;
constexpr uint32_t SM_WA = 180224;
constexpr uint32_t SM_STG = 212992;
constexpr uint32_t SM_BAR = 229376;
constexpr uint32_t SM_STAT = SM_BAR + 512;
constexpr uint32_t SM_ORDER = SM_STAT + 16;
constexpr uint32_t SM_EYE = SM_BAR + 1024;
constexpr uint32_t SMEM_BYTES = SM_BAR + 2048 + 1024;

enum {
  B_FULLH = 0, B_EMPTYH = 4, B_FULLKV = 7, B_EMPTYKV = 11, B_OWNRDY = 15, B_STOREDONE = 16, B_STOREDONE1 = 17,
  B_FULLXA = 18, B_FULLWA = 25, B_EMPTYWA = 29, B_XAFREE = 33, B_STGFREE = 34, B_STATS = 35, B_ATTNDONE = 36,
  B_FULLWOB = 37, B_LOOPDONE = 38, B_PUBA = 39, B_EMPTYXA = 40, B_FULLOB = 47, B_H3FREE = 55, B_H1FREE = 56, B_COUNT = 57
};

enum { F_KV = 0, F_OA = 256, F_OB = 384, F_COUNT = 512 };
__device__ __align__(1024) __half g_kv[16 * S_LEN * 64];
__device__ __align__(1024) __nv_bfloat16 g_oA[S_LEN * 512];
__device__ __align__(1024) __nv_bfloat16 g_oB[S_LEN * 512];
__device__ __align__(1024) uint4 g_part[8 * 16 * 56 * 32];
__device__ __align__(1024) uint2 g_kvf[8 * 64 * 32];
__device__ __align__(1024) unsigned long long g_stats[8 * 64 * 2];
__device__ __align__(1024) unsigned g_flags[F_COUNT];
__device__ unsigned g_epoch = 1;
#define TSTAMP(i) do {} while (0)
#define GSTAMP(i) do {} while (0)
#define TDUMP() do {} while (0)
#define ISTAMP(i, v) do {} while (0)

struct __align__(64) Params {
  CUtensorMap xB, wBh, xA, wA, woA, woB, kv, oA, oB, outs;
  const __nv_bfloat16* xBp;
  const __nv_bfloat16* wBp;
  uint4* part;
  uint2* kvf;
  unsigned long long* stats;
  unsigned* flags;
  unsigned* epoch;
  int force_slow;
  uint32_t zero;
};

constexpr uint32_t SPIN_LIMIT = 1u << 24;
#define AWAIT 3
#define AFLY 2
#define OHALF 1
#define AEARLY 1
#define WORD 0
#define WOFF 0
#define BBK 0
#define AGRP 2
constexpr bool A_ON = true;

__device__ __forceinline__ void trap_now() { asm volatile("st.global.u32 [%0], %1;" ::"l"(0ull), "r"(0) : "memory"); }
__device__ __forceinline__ void mbar_init(uint32_t a, uint32_t c) {
  asm volatile("mbarrier.init.shared::cta.b64 [%0], %1;" ::"r"(a), "r"(c));
}
__device__ __forceinline__ void mbar_expect(uint32_t a, uint32_t bytes) {
  asm volatile("mbarrier.arrive.expect_tx.shared::cta.b64 _, [%0], %1;" ::"r"(a), "r"(bytes) : "memory");
}
__device__ __forceinline__ void mbar_arrive(uint32_t a) {
  asm volatile("mbarrier.arrive.shared::cta.b64 _, [%0];" ::"r"(a) : "memory");
}
__device__ __forceinline__ void mbar_arrive_if(uint32_t a, bool c) {
  asm volatile("{\n.reg .pred p;\nsetp.ne.b32 p, %1, 0;\n@p mbarrier.arrive.shared::cta.b64 _, [%0];\n}" ::"r"(a),
               "r"((uint32_t)c) : "memory");
}
__device__ __forceinline__ void mbar_arrive_cluster_if(uint32_t a, bool c) {
  asm volatile("{\n.reg .pred p;\nsetp.ne.b32 p, %1, 0;\n@p mbarrier.arrive.shared::cluster.b64 _, [%0];\n}" ::"r"(a),
               "r"((uint32_t)c) : "memory");
}
__device__ __forceinline__ uint32_t mbar_test(uint32_t a, uint32_t parity) {
  uint32_t ok;
  asm volatile("{\n.reg .pred p;\nmbarrier.test_wait.parity.shared::cta.b64 p, [%1], %2;\nselp.u32 %0, 1, 0, p;\n}"
               : "=r"(ok) : "r"(a), "r"(parity) : "memory");
  return ok;
}
__device__ __forceinline__ void mbar_wait(uint32_t a, uint32_t parity, uint32_t have = 0) {
  asm volatile(
      "{\n.reg .pred p;\nsetp.ne.u32 p, %2, 0;\n@p bra.uni DONE;\n"
      "SPIN:\nmbarrier.try_wait.parity.shared::cta.b64 p, [%0], %1;\n@!p bra.uni SPIN;\nDONE:\n}"
      ::"r"(a), "r"(parity), "r"(have) : "memory");
}
__device__ __forceinline__ uint32_t mapa(uint32_t a, uint32_t rank) {
  uint32_t r;
  asm("mapa.shared::cluster.u32 %0, %1, %2;" : "=r"(r) : "r"(a), "r"(rank));
  return r;
}
__device__ __forceinline__ bool elect() {
  uint32_t p;
  asm volatile("{\n.reg .pred P;\nelect.sync _|P, 0xffffffff;\nselp.u32 %0, 1, 0, P;\n}" : "=r"(p));
  return p;
}
__device__ __forceinline__ void tma_load(uint32_t dst, const CUtensorMap* m, int c0, int c1, uint32_t bar) {
  asm volatile("cp.async.bulk.tensor.2d.shared::cluster.global.mbarrier::complete_tx::bytes [%0], [%1, {%3, %4}], [%2];"
               ::"r"(dst), "l"(m), "r"(bar), "r"(c0), "r"(c1) : "memory");
}
__device__ __forceinline__ void tma_load_mc(uint32_t dst, const CUtensorMap* m, int c0, int c1, uint32_t bar) {
  asm volatile(
      "cp.async.bulk.tensor.2d.shared::cluster.global.mbarrier::complete_tx::bytes.multicast::cluster [%0], [%1, {%3, %4}], [%2], %5;"
      ::"r"(dst), "l"(m), "r"(bar), "r"(c0), "r"(c1), "h"((uint16_t)3) : "memory");
}
__device__ __forceinline__ void tma_store(const CUtensorMap* m, int c0, int c1, uint32_t src) {
  asm volatile("cp.async.bulk.tensor.2d.global.shared::cta.bulk_group [%0, {%2, %3}], [%1];" ::"l"(m), "r"(src),
               "r"(c0), "r"(c1) : "memory");
}
__device__ __forceinline__ void tma_prefetch_l2(const CUtensorMap* m, int c0, int c1) {
  asm volatile("cp.async.bulk.prefetch.tensor.2d.L2.global [%0, {%1, %2}];" ::"l"(m), "r"(c0), "r"(c1) : "memory");
}
__device__ __forceinline__ void prefetch_map(const CUtensorMap* m) {
  asm volatile("prefetch.tensormap [%0];" ::"l"(m) : "memory");
}
__device__ __forceinline__ void fence_async_smem() { asm volatile("fence.proxy.async.shared::cta;" ::: "memory"); }
__device__ __forceinline__ void fence_async_all() { asm volatile("fence.proxy.async.global;" ::: "memory"); }
__device__ __forceinline__ void named_sync(int id, int n) { asm volatile("bar.sync %0, %1;" ::"r"(id), "r"(n) : "memory"); }
__device__ __forceinline__ bool named_or(int id, int n, bool v) {
  uint32_t r;
  asm volatile("{\n.reg .pred p, q;\nsetp.ne.b32 p, %3, 0;\nbarrier.red.or.pred q, %1, %2, p;\nselp.u32 %0, 1, 0, q;\n}"
               : "=r"(r) : "r"(id), "r"(n), "r"((uint32_t)v) : "memory");
  return r;
}
__device__ __forceinline__ unsigned ld_flag(const unsigned* p) {
  unsigned v;
  asm volatile("ld.relaxed.gpu.global.u32 %0, [%1];" : "=r"(v) : "l"(p) : "memory");
  return v;
}
__device__ __forceinline__ void bulk_commit() { asm volatile("cp.async.bulk.commit_group;" ::: "memory"); }
__device__ __forceinline__ void bulk_wait() {
  asm volatile("cp.async.bulk.wait_group 0;" ::: "memory");
  asm volatile("fence.proxy.async.global;" ::: "memory");
}
__device__ __forceinline__ void st_release(unsigned* p, unsigned v) {
  asm volatile("st.release.gpu.global.u32 [%0], %1;" ::"l"(p), "r"(v) : "memory");
}
__device__ __forceinline__ void poll_flags(const unsigned* flags, int n, unsigned tag, int lane) {
  uint32_t it = 0;
  while (true) {
    bool ok = lane >= n || ld_flag(flags + lane) == tag;
    if (__all_sync(0xffffffffu, ok)) break;
    if (++it > SPIN_LIMIT) trap_now();
  }
  __syncwarp();
}

__device__ __forceinline__ void poll_tags(const unsigned* w, unsigned tag) {
  uint32_t it = 0;
  while (!__all_sync(0xffffffffu, ld_flag(w) == tag)) {
    if (++it > SPIN_LIMIT) trap_now();
    __nanosleep(300);
  }
}
__device__ __forceinline__ void wg_fence() { asm volatile("wgmma.fence.sync.aligned;" ::: "memory"); }
__device__ __forceinline__ void wg_commit() { asm volatile("wgmma.commit_group.sync.aligned;" ::: "memory"); }
template <int N> __device__ __forceinline__ void wg_wait() { asm volatile("wgmma.wait_group.sync.aligned %0;" ::"n"(N) : "memory"); }
template <int N> __device__ __forceinline__ void pin(float (&a)[N]) {
#pragma unroll
  for (int i = 0; i < N; i++) asm volatile("" : "+f"(a[i])::"memory");
}
template <int N> __device__ __forceinline__ void pin(uint32_t (&a)[N]) {
#pragma unroll
  for (int i = 0; i < N; i++) asm volatile("" : "+r"(a[i])::"memory");
}
__device__ __forceinline__ uint64_t desc(uint32_t lo) { return (uint64_t)0x40000040u << 32 | lo; }
__device__ __forceinline__ uint32_t desc_lo(uint32_t addr, uint32_t lbo) { return ((addr & 0x3FFFF) >> 4) | ((lbo >> 4) << 16); }

__device__ __forceinline__ void stsm4(uint32_t addr, uint32_t r0, uint32_t r1, uint32_t r2, uint32_t r3) {
  asm volatile("stmatrix.sync.aligned.m8n8.x4.shared.b16 [%0], {%1, %2, %3, %4};" ::"r"(addr), "r"(r0), "r"(r1),
               "r"(r2), "r"(r3) : "memory");
}
__device__ __forceinline__ void stsm2(uint32_t addr, uint32_t r0, uint32_t r1) {
  asm volatile("stmatrix.sync.aligned.m8n8.x2.shared.b16 [%0], {%1, %2};" ::"r"(addr), "r"(r0), "r"(r1) : "memory");
}
__device__ __forceinline__ void stage56(uint32_t base, const uint32_t (&v)[14], int lane) {
  const uint32_t a = base + (lane & 15) * 112 + (lane >> 4) * 16;
  stsm4(a, v[0], v[1], v[2], v[3]);
  stsm4(a + 32, v[4], v[5], v[6], v[7]);
  stsm4(a + 64, v[8], v[9], v[10], v[11]);
  stsm2(a + 96, v[12], v[13]);
}
__device__ __forceinline__ void stage64(uint32_t base, const uint32_t (&v)[14], int lane, int off) {
  const uint32_t a = base + (lane & 15) * 128, c = off + (lane >> 4), x = lane & 7;
  stsm4(a + ((c ^ x) << 4), v[0], v[1], v[2], v[3]);
  stsm4(a + (((c + 2) ^ x) << 4), v[4], v[5], v[6], v[7]);
  stsm4(a + (((c + 4) ^ x) << 4), v[8], v[9], v[10], v[11]);
  stsm4(a + ((((c + 6) & 7) ^ x) << 4), v[12], v[13], 0, 0);
}
__device__ __forceinline__ uint32_t pack_h(float lo, float hi) {
  uint32_t r;
  asm("cvt.rn.f16x2.f32 %0, %1, %2;" : "=r"(r) : "f"(hi), "f"(lo));
  return r;
}
__device__ __forceinline__ uint32_t pack_b(float lo, float hi) {
  uint32_t r;
  asm("cvt.rn.bf16x2.f32 %0, %1, %2;" : "=r"(r) : "f"(hi), "f"(lo));
  return r;
}
__device__ __forceinline__ uint32_t ex2_h2(uint32_t x) {
  uint32_t y;
  asm("ex2.approx.f16x2 %0, %1;" : "=r"(y) : "r"(x));
  return y;
}
__device__ __forceinline__ float ex2_f(float x) {
  float y;
  asm("ex2.approx.ftz.f32 %0, %1;" : "=f"(y) : "f"(x));
  return y;
}
__device__ __forceinline__ float rcp_f(float x) {
  float y;
  asm("rcp.approx.f32 %0, %1;" : "=f"(y) : "f"(x));
  return y;
}
__device__ __forceinline__ uint32_t hfma2(uint32_t a, uint32_t b, uint32_t c) {
  uint32_t y;
  asm("fma.rn.f16x2 %0, %1, %2, %3;" : "=r"(y) : "r"(a), "r"(b), "r"(c));
  return y;
}
__device__ __forceinline__ uint32_t habsmax2(uint32_t m, uint32_t a) {
  uint32_t y;
  asm("max.f16x2 %0, %1, %2;" : "=r"(y) : "r"(m), "r"(a & 0x7fff7fffu));
  return y;
}
__device__ __forceinline__ float h_lo(uint32_t v) { return __half2float(__ushort_as_half((unsigned short)(v & 0xffff))); }
__device__ __forceinline__ float h_hi(uint32_t v) { return __half2float(__ushort_as_half((unsigned short)(v >> 16))); }
__device__ __forceinline__ uint32_t phi2(float a, float b) {
  const float ea = ex2_f(fminf(a * 1.4426950408889634f, 0.f)), eb = ex2_f(fminf(b * 1.4426950408889634f, 0.f));
  return pack_b(fmaxf(a, 0.f) + ea + 1e-6f, fmaxf(b, 0.f) + eb + 1e-6f);
}

__device__ __forceinline__ void mma_n192_ss_tb(float (&d)[96], uint64_t a, uint64_t b, int acc) {
  asm volatile("{\n.reg .pred p;\nsetp.ne.b32 p, %98, 0;\n"
    "wgmma.mma_async.sync.aligned.m64n192k16.f32.bf16.bf16 "
    "{%0,%1,%2,%3,%4,%5,%6,%7,%8,%9,%10,%11,%12,%13,%14,%15,%16,%17,%18,%19,%20,%21,%22,%23,%24,%25,%26,%27,%28,%29,%30,%31,%32,%33,%34,%35,%36,%37,%38,%39,%40,%41,%42,%43,%44,%45,%46,%47,%48,%49,%50,%51,%52,%53,%54,%55,%56,%57,%58,%59,%60,%61,%62,%63,%64,%65,%66,%67,%68,%69,%70,%71,%72,%73,%74,%75,%76,%77,%78,%79,%80,%81,%82,%83,%84,%85,%86,%87,%88,%89,%90,%91,%92,%93,%94,%95}, "
    "%96, %97, p, 1, 1, 0, 1;\n}\n"
    : "+f"(d[0]), "+f"(d[1]), "+f"(d[2]), "+f"(d[3]), "+f"(d[4]), "+f"(d[5]), "+f"(d[6]), "+f"(d[7]),
      "+f"(d[8]), "+f"(d[9]), "+f"(d[10]), "+f"(d[11]), "+f"(d[12]), "+f"(d[13]), "+f"(d[14]), "+f"(d[15]),
      "+f"(d[16]), "+f"(d[17]), "+f"(d[18]), "+f"(d[19]), "+f"(d[20]), "+f"(d[21]), "+f"(d[22]), "+f"(d[23]),
      "+f"(d[24]), "+f"(d[25]), "+f"(d[26]), "+f"(d[27]), "+f"(d[28]), "+f"(d[29]), "+f"(d[30]), "+f"(d[31]),
      "+f"(d[32]), "+f"(d[33]), "+f"(d[34]), "+f"(d[35]), "+f"(d[36]), "+f"(d[37]), "+f"(d[38]), "+f"(d[39]),
      "+f"(d[40]), "+f"(d[41]), "+f"(d[42]), "+f"(d[43]), "+f"(d[44]), "+f"(d[45]), "+f"(d[46]), "+f"(d[47]),
      "+f"(d[48]), "+f"(d[49]), "+f"(d[50]), "+f"(d[51]), "+f"(d[52]), "+f"(d[53]), "+f"(d[54]), "+f"(d[55]),
      "+f"(d[56]), "+f"(d[57]), "+f"(d[58]), "+f"(d[59]), "+f"(d[60]), "+f"(d[61]), "+f"(d[62]), "+f"(d[63]),
      "+f"(d[64]), "+f"(d[65]), "+f"(d[66]), "+f"(d[67]), "+f"(d[68]), "+f"(d[69]), "+f"(d[70]), "+f"(d[71]),
      "+f"(d[72]), "+f"(d[73]), "+f"(d[74]), "+f"(d[75]), "+f"(d[76]), "+f"(d[77]), "+f"(d[78]), "+f"(d[79]),
      "+f"(d[80]), "+f"(d[81]), "+f"(d[82]), "+f"(d[83]), "+f"(d[84]), "+f"(d[85]), "+f"(d[86]), "+f"(d[87]),
      "+f"(d[88]), "+f"(d[89]), "+f"(d[90]), "+f"(d[91]), "+f"(d[92]), "+f"(d[93]), "+f"(d[94]), "+f"(d[95])
    : "l"(a), "l"(b), "r"(acc));
}
__device__ __forceinline__ void mma_qk(uint32_t (&d)[16], uint32_t a0, uint32_t a1, uint32_t a2, uint32_t a3, uint64_t b, int acc) {
  asm volatile("{\n.reg .pred p;\nsetp.ne.b32 p, %21, 0;\n"
    "wgmma.mma_async.sync.aligned.m64n64k16.f16.f16.f16 "
    "{%0,%1,%2,%3,%4,%5,%6,%7,%8,%9,%10,%11,%12,%13,%14,%15}, "
    "{%16,%17,%18,%19}, %20, p, 1, 1, 0;\n}\n"
    : "+r"(d[0]), "+r"(d[1]), "+r"(d[2]), "+r"(d[3]), "+r"(d[4]), "+r"(d[5]), "+r"(d[6]), "+r"(d[7]),
      "+r"(d[8]), "+r"(d[9]), "+r"(d[10]), "+r"(d[11]), "+r"(d[12]), "+r"(d[13]), "+r"(d[14]), "+r"(d[15])
    : "r"(a0), "r"(a1), "r"(a2), "r"(a3), "l"(b), "r"(acc));
}
__device__ __forceinline__ void mma_qk0(uint32_t (&d)[16], uint32_t a0, uint32_t a1, uint32_t a2, uint32_t a3, uint64_t b) {
  asm volatile("{\n.reg .pred p;\nsetp.ne.b32 p, %21, 0;\n"
    "wgmma.mma_async.sync.aligned.m64n64k16.f16.f16.f16 "
    "{%0,%1,%2,%3,%4,%5,%6,%7,%8,%9,%10,%11,%12,%13,%14,%15}, "
    "{%16,%17,%18,%19}, %20, p, 1, 1, 0;\n}\n"
    : "=r"(d[0]), "=r"(d[1]), "=r"(d[2]), "=r"(d[3]), "=r"(d[4]), "=r"(d[5]), "=r"(d[6]), "=r"(d[7]),
      "=r"(d[8]), "=r"(d[9]), "=r"(d[10]), "=r"(d[11]), "=r"(d[12]), "=r"(d[13]), "=r"(d[14]), "=r"(d[15])
    : "r"(a0), "r"(a1), "r"(a2), "r"(a3), "l"(b), "n"(0));
}
__device__ __forceinline__ void mma_pv_h0(uint32_t (&d)[8], uint32_t a0, uint32_t a1, uint32_t a2, uint32_t a3, uint64_t b) {
  asm volatile("{\n.reg .pred p;\nsetp.ne.b32 p, %13, 0;\n"
    "wgmma.mma_async.sync.aligned.m64n32k16.f16.f16.f16 "
    "{%0,%1,%2,%3,%4,%5,%6,%7}, "
    "{%8,%9,%10,%11}, %12, p, 1, 1, 1;\n}\n"
    : "=r"(d[0]), "=r"(d[1]), "=r"(d[2]), "=r"(d[3]), "=r"(d[4]), "=r"(d[5]), "=r"(d[6]), "=r"(d[7])
    : "r"(a0), "r"(a1), "r"(a2), "r"(a3), "l"(b), "n"(0));
}
__device__ __forceinline__ void mma_pv(float (&d)[16], uint32_t a0, uint32_t a1, uint32_t a2, uint32_t a3, uint64_t b, int acc) {
  asm volatile("{\n.reg .pred p;\nsetp.ne.b32 p, %21, 0;\n"
    "wgmma.mma_async.sync.aligned.m64n32k16.f32.f16.f16 "
    "{%0,%1,%2,%3,%4,%5,%6,%7,%8,%9,%10,%11,%12,%13,%14,%15}, "
    "{%16,%17,%18,%19}, %20, p, 1, 1, 1;\n}\n"
    : "+f"(d[0]), "+f"(d[1]), "+f"(d[2]), "+f"(d[3]), "+f"(d[4]), "+f"(d[5]), "+f"(d[6]), "+f"(d[7]),
      "+f"(d[8]), "+f"(d[9]), "+f"(d[10]), "+f"(d[11]), "+f"(d[12]), "+f"(d[13]), "+f"(d[14]), "+f"(d[15])
    : "r"(a0), "r"(a1), "r"(a2), "r"(a3), "l"(b), "r"(acc));
}
__device__ __forceinline__ void mma_pv_h(uint32_t (&d)[8], uint32_t a0, uint32_t a1, uint32_t a2, uint32_t a3, uint64_t b, int acc) {
  asm volatile("{\n.reg .pred p;\nsetp.ne.b32 p, %13, 0;\n"
    "wgmma.mma_async.sync.aligned.m64n32k16.f16.f16.f16 "
    "{%0,%1,%2,%3,%4,%5,%6,%7}, "
    "{%8,%9,%10,%11}, %12, p, 1, 1, 1;\n}\n"
    : "+r"(d[0]), "+r"(d[1]), "+r"(d[2]), "+r"(d[3]), "+r"(d[4]), "+r"(d[5]), "+r"(d[6]), "+r"(d[7])
    : "r"(a0), "r"(a1), "r"(a2), "r"(a3), "l"(b), "r"(acc));
}
__device__ __forceinline__ void mma_fl(float (&d)[8], uint32_t a0, uint32_t a1, uint32_t a2, uint32_t a3, uint64_t b, int acc) {
  asm volatile("{\n.reg .pred p;\nsetp.ne.b32 p, %13, 0;\n"
    "wgmma.mma_async.sync.aligned.m64n16k16.f32.f16.f16 "
    "{%0,%1,%2,%3,%4,%5,%6,%7}, "
    "{%8,%9,%10,%11}, %12, p, 1, 1, 0;\n}\n"
    : "+f"(d[0]), "+f"(d[1]), "+f"(d[2]), "+f"(d[3]), "+f"(d[4]), "+f"(d[5]), "+f"(d[6]), "+f"(d[7])
    : "r"(a0), "r"(a1), "r"(a2), "r"(a3), "l"(b), "r"(acc));
}
__device__ __forceinline__ void mma_n128_ss_ta(float (&d)[64], uint64_t a, uint64_t b, int acc) {
  asm volatile("{\n.reg .pred p;\nsetp.ne.b32 p, %66, 0;\n"
    "wgmma.mma_async.sync.aligned.m64n128k16.f32.bf16.bf16 "
    "{%0,%1,%2,%3,%4,%5,%6,%7,%8,%9,%10,%11,%12,%13,%14,%15,%16,%17,%18,%19,%20,%21,%22,%23,%24,%25,%26,%27,%28,%29,%30,%31,%32,%33,%34,%35,%36,%37,%38,%39,%40,%41,%42,%43,%44,%45,%46,%47,%48,%49,%50,%51,%52,%53,%54,%55,%56,%57,%58,%59,%60,%61,%62,%63}, "
    "%64, %65, p, 1, 1, 1, 0;\n}\n"
    : "+f"(d[0]), "+f"(d[1]), "+f"(d[2]), "+f"(d[3]), "+f"(d[4]), "+f"(d[5]), "+f"(d[6]), "+f"(d[7]),
      "+f"(d[8]), "+f"(d[9]), "+f"(d[10]), "+f"(d[11]), "+f"(d[12]), "+f"(d[13]), "+f"(d[14]), "+f"(d[15]),
      "+f"(d[16]), "+f"(d[17]), "+f"(d[18]), "+f"(d[19]), "+f"(d[20]), "+f"(d[21]), "+f"(d[22]), "+f"(d[23]),
      "+f"(d[24]), "+f"(d[25]), "+f"(d[26]), "+f"(d[27]), "+f"(d[28]), "+f"(d[29]), "+f"(d[30]), "+f"(d[31]),
      "+f"(d[32]), "+f"(d[33]), "+f"(d[34]), "+f"(d[35]), "+f"(d[36]), "+f"(d[37]), "+f"(d[38]), "+f"(d[39]),
      "+f"(d[40]), "+f"(d[41]), "+f"(d[42]), "+f"(d[43]), "+f"(d[44]), "+f"(d[45]), "+f"(d[46]), "+f"(d[47]),
      "+f"(d[48]), "+f"(d[49]), "+f"(d[50]), "+f"(d[51]), "+f"(d[52]), "+f"(d[53]), "+f"(d[54]), "+f"(d[55]),
      "+f"(d[56]), "+f"(d[57]), "+f"(d[58]), "+f"(d[59]), "+f"(d[60]), "+f"(d[61]), "+f"(d[62]), "+f"(d[63])
    : "l"(a), "l"(b), "r"(acc));
}
__device__ __forceinline__ void mma_n64_rs(float (&d)[32], uint32_t a0, uint32_t a1, uint32_t a2, uint32_t a3, uint64_t b, int acc) {
  asm volatile("{\n.reg .pred p;\nsetp.ne.b32 p, %37, 0;\n"
    "wgmma.mma_async.sync.aligned.m64n64k16.f32.bf16.bf16 "
    "{%0,%1,%2,%3,%4,%5,%6,%7,%8,%9,%10,%11,%12,%13,%14,%15,%16,%17,%18,%19,%20,%21,%22,%23,%24,%25,%26,%27,%28,%29,%30,%31}, "
    "{%32,%33,%34,%35}, %36, p, 1, 1, 0;\n}\n"
    : "+f"(d[0]), "+f"(d[1]), "+f"(d[2]), "+f"(d[3]), "+f"(d[4]), "+f"(d[5]), "+f"(d[6]), "+f"(d[7]),
      "+f"(d[8]), "+f"(d[9]), "+f"(d[10]), "+f"(d[11]), "+f"(d[12]), "+f"(d[13]), "+f"(d[14]), "+f"(d[15]),
      "+f"(d[16]), "+f"(d[17]), "+f"(d[18]), "+f"(d[19]), "+f"(d[20]), "+f"(d[21]), "+f"(d[22]), "+f"(d[23]),
      "+f"(d[24]), "+f"(d[25]), "+f"(d[26]), "+f"(d[27]), "+f"(d[28]), "+f"(d[29]), "+f"(d[30]), "+f"(d[31])
    : "r"(a0), "r"(a1), "r"(a2), "r"(a3), "l"(b), "r"(acc));
}
__device__ __forceinline__ void mma_n64_rs_tb(float (&d)[32], uint32_t a0, uint32_t a1, uint32_t a2, uint32_t a3, uint64_t b, int acc) {
  asm volatile("{\n.reg .pred p;\nsetp.ne.b32 p, %37, 0;\n"
    "wgmma.mma_async.sync.aligned.m64n64k16.f32.bf16.bf16 "
    "{%0,%1,%2,%3,%4,%5,%6,%7,%8,%9,%10,%11,%12,%13,%14,%15,%16,%17,%18,%19,%20,%21,%22,%23,%24,%25,%26,%27,%28,%29,%30,%31}, "
    "{%32,%33,%34,%35}, %36, p, 1, 1, 1;\n}\n"
    : "+f"(d[0]), "+f"(d[1]), "+f"(d[2]), "+f"(d[3]), "+f"(d[4]), "+f"(d[5]), "+f"(d[6]), "+f"(d[7]),
      "+f"(d[8]), "+f"(d[9]), "+f"(d[10]), "+f"(d[11]), "+f"(d[12]), "+f"(d[13]), "+f"(d[14]), "+f"(d[15]),
      "+f"(d[16]), "+f"(d[17]), "+f"(d[18]), "+f"(d[19]), "+f"(d[20]), "+f"(d[21]), "+f"(d[22]), "+f"(d[23]),
      "+f"(d[24]), "+f"(d[25]), "+f"(d[26]), "+f"(d[27]), "+f"(d[28]), "+f"(d[29]), "+f"(d[30]), "+f"(d[31])
    : "r"(a0), "r"(a1), "r"(a2), "r"(a3), "l"(b), "r"(acc));
}
__device__ __forceinline__ void mma_n64_ss_tb(float (&d)[32], uint64_t a, uint64_t b, int acc) {
  asm volatile("{\n.reg .pred p;\nsetp.ne.b32 p, %34, 0;\n"
    "wgmma.mma_async.sync.aligned.m64n64k16.f32.bf16.bf16 "
    "{%0,%1,%2,%3,%4,%5,%6,%7,%8,%9,%10,%11,%12,%13,%14,%15,%16,%17,%18,%19,%20,%21,%22,%23,%24,%25,%26,%27,%28,%29,%30,%31}, "
    "%32, %33, p, 1, 1, 0, 1;\n}\n"
    : "+f"(d[0]), "+f"(d[1]), "+f"(d[2]), "+f"(d[3]), "+f"(d[4]), "+f"(d[5]), "+f"(d[6]), "+f"(d[7]),
      "+f"(d[8]), "+f"(d[9]), "+f"(d[10]), "+f"(d[11]), "+f"(d[12]), "+f"(d[13]), "+f"(d[14]), "+f"(d[15]),
      "+f"(d[16]), "+f"(d[17]), "+f"(d[18]), "+f"(d[19]), "+f"(d[20]), "+f"(d[21]), "+f"(d[22]), "+f"(d[23]),
      "+f"(d[24]), "+f"(d[25]), "+f"(d[26]), "+f"(d[27]), "+f"(d[28]), "+f"(d[29]), "+f"(d[30]), "+f"(d[31])
    : "l"(a), "l"(b), "r"(acc));
}
__device__ __forceinline__ void mma_n112_ss_tb(float (&d)[56], uint64_t a, uint64_t b, int acc) {
  asm volatile("{\n.reg .pred p;\nsetp.ne.b32 p, %58, 0;\n"
    "wgmma.mma_async.sync.aligned.m64n112k16.f32.bf16.bf16 "
    "{%0,%1,%2,%3,%4,%5,%6,%7,%8,%9,%10,%11,%12,%13,%14,%15,%16,%17,%18,%19,%20,%21,%22,%23,%24,%25,%26,%27,%28,%29,%30,%31,%32,%33,%34,%35,%36,%37,%38,%39,%40,%41,%42,%43,%44,%45,%46,%47,%48,%49,%50,%51,%52,%53,%54,%55}, "
    "%56, %57, p, 1, 1, 0, 1;\n}\n"
    : "+f"(d[0]), "+f"(d[1]), "+f"(d[2]), "+f"(d[3]), "+f"(d[4]), "+f"(d[5]), "+f"(d[6]), "+f"(d[7]),
      "+f"(d[8]), "+f"(d[9]), "+f"(d[10]), "+f"(d[11]), "+f"(d[12]), "+f"(d[13]), "+f"(d[14]), "+f"(d[15]),
      "+f"(d[16]), "+f"(d[17]), "+f"(d[18]), "+f"(d[19]), "+f"(d[20]), "+f"(d[21]), "+f"(d[22]), "+f"(d[23]),
      "+f"(d[24]), "+f"(d[25]), "+f"(d[26]), "+f"(d[27]), "+f"(d[28]), "+f"(d[29]), "+f"(d[30]), "+f"(d[31]),
      "+f"(d[32]), "+f"(d[33]), "+f"(d[34]), "+f"(d[35]), "+f"(d[36]), "+f"(d[37]), "+f"(d[38]), "+f"(d[39]),
      "+f"(d[40]), "+f"(d[41]), "+f"(d[42]), "+f"(d[43]), "+f"(d[44]), "+f"(d[45]), "+f"(d[46]), "+f"(d[47]),
      "+f"(d[48]), "+f"(d[49]), "+f"(d[50]), "+f"(d[51]), "+f"(d[52]), "+f"(d[53]), "+f"(d[54]), "+f"(d[55])
    : "l"(a), "l"(b), "r"(acc));
}
__device__ __forceinline__ void mma_n56_ss_tb(float (&d)[28], uint64_t a, uint64_t b, int acc) {
  asm volatile("{\n.reg .pred p;\nsetp.ne.b32 p, %30, 0;\n"
    "wgmma.mma_async.sync.aligned.m64n56k16.f32.bf16.bf16 "
    "{%0,%1,%2,%3,%4,%5,%6,%7,%8,%9,%10,%11,%12,%13,%14,%15,%16,%17,%18,%19,%20,%21,%22,%23,%24,%25,%26,%27}, "
    "%28, %29, p, 1, 1, 0, 1;\n}\n"
    : "+f"(d[0]), "+f"(d[1]), "+f"(d[2]), "+f"(d[3]), "+f"(d[4]), "+f"(d[5]), "+f"(d[6]), "+f"(d[7]),
      "+f"(d[8]), "+f"(d[9]), "+f"(d[10]), "+f"(d[11]), "+f"(d[12]), "+f"(d[13]), "+f"(d[14]), "+f"(d[15]),
      "+f"(d[16]), "+f"(d[17]), "+f"(d[18]), "+f"(d[19]), "+f"(d[20]), "+f"(d[21]), "+f"(d[22]), "+f"(d[23]),
      "+f"(d[24]), "+f"(d[25]), "+f"(d[26]), "+f"(d[27])
    : "l"(a), "l"(b), "r"(acc));
}

#define NPOLY 5
#define PGROUP 1
__device__ __forceinline__ uint32_t exp2_fma_h2(uint32_t x, uint32_t magic, uint32_t& chain) {
  uint32_t c, t, n, f;
  asm("min.xorsign.abs.f16x2 %0, %1, %2;" : "=r"(c) : "r"(x), "r"(0x4b004b00u));
  asm("add.rn.f16x2 %0, %1, %2;" : "=r"(t) : "r"(c), "r"(magic));
  asm("sub.rn.f16x2 %0, %1, %2;" : "=r"(n) : "r"(t), "r"(0x66006600u));
  asm("sub.rn.f16x2 %0, %1, %2;" : "=r"(f) : "r"(c), "r"(n));
  uint32_t q = hfma2(0x2af92af9u, f, 0x33be33beu);
  q = hfma2(q, f, 0x398c398cu);
  q = hfma2(q, f, 0x3c003c00u);
  chain = q;
  return q + (t << 10) - 0x01980000u;
}
__device__ __forceinline__ void exp_tile(const uint32_t (&s)[16], uint32_t (&p)[16], uint32_t zero, uint32_t& chain) {
  uint32_t magic = 0x66006600u;
#pragma unroll
  for (int i = 0; i < 16; i++) {
    const int k = i * NPOLY / 16;
    if ((i + 1) * NPOLY / 16 != k) {
      if (k % PGROUP == 0) magic = hfma2(chain, zero, 0x66006600u);
      p[i] = exp2_fma_h2(s[i], magic, chain);
    } else {
      p[i] = ex2_h2(s[i]);
    }
  }
}

__device__ __forceinline__ void slow_project(const __nv_bfloat16* __restrict__ xrow, const __nv_bfloat16* __restrict__ wcol,
                                             float (&o)[DH]) {
#pragma unroll
  for (int d = 0; d < DH; d++) o[d] = 0.f;
#pragma unroll 1
  for (int k = 0; k < DM; k += 2) {
    __nv_bfloat162 xv = *reinterpret_cast<const __nv_bfloat162*>(xrow + k);
#pragma unroll
    for (int u = 0; u < 2; u++) {
      float x = u ? __high2float(xv) : __low2float(xv);
      const uint2* wp = reinterpret_cast<const uint2*>(wcol + (size_t)(k + u) * (3 * DM));
#pragma unroll
      for (int d = 0; d < DH / 4; d++) {
        uint2 w = __ldg(wp + d);
        o[4 * d + 0] = fmaf(x, __uint_as_float(w.x << 16), o[4 * d + 0]);
        o[4 * d + 1] = fmaf(x, __uint_as_float(w.x & 0xffff0000u), o[4 * d + 1]);
        o[4 * d + 2] = fmaf(x, __uint_as_float(w.y << 16), o[4 * d + 2]);
        o[4 * d + 3] = fmaf(x, __uint_as_float(w.y & 0xffff0000u), o[4 * d + 3]);
      }
    }
  }
#pragma unroll
  for (int d = 0; d < DH; d++) o[d] = __bfloat162float(__float2bfloat16(o[d]));
}

__device__ __forceinline__ void slow_attention(const __nv_bfloat16* __restrict__ x, const __nv_bfloat16* __restrict__ w,
                                            float* scratch, uint32_t* stage, int row0, int p, int t, int bar_id) {
  const int head = 2 * p + (t >> 6), row = row0 + (t & 63);
  float q[DH], acc[DH], tmp[DH];
  slow_project(x + (size_t)row * DM, w + head * DH, q);
  float m = -INFINITY, l = 0.f;
#pragma unroll
  for (int d = 0; d < DH; d++) acc[d] = 0.f;
  float* mine = scratch + t * (2 * DH + 1);
  const float* keys = scratch + (t >> 6) * 64 * (2 * DH + 1);
#pragma unroll 1
  for (int kb = 0; kb < S_LEN; kb += 64) {
#pragma unroll 1
    for (int part = 0; part < 2; part++) {
      slow_project(x + (size_t)(kb + (t & 63)) * DM, w + (part + 1) * DM + head * DH, tmp);
#pragma unroll
      for (int d = 0; d < DH; d++) mine[part * DH + d] = tmp[d];
    }
    named_sync(bar_id, 128);
#pragma unroll 1
    for (int j = 0; j < 64; j++) {
      const float* kr = keys + j * (2 * DH + 1);
      float s = 0.f;
#pragma unroll
      for (int d = 0; d < DH; d++) s = fmaf(q[d], kr[d], s);
      s *= 0.18898223650461362f;
      float mn = fmaxf(m, s);
      float a = __expf(m - mn), pj = __expf(s - mn);
      l = l * a + pj;
#pragma unroll
      for (int d = 0; d < DH; d++) acc[d] = fmaf(pj, kr[DH + d], acc[d] * a);
      m = mn;
    }
    named_sync(bar_id, 128);
  }
  float r = rcp_f(l);
#pragma unroll
  for (int d = 0; d < DH; d += 2) {
    const int w = (p == 7) * 4 + (t >> 6) * 14 + (d >> 1);
    stage[(t & 63) * 32 + (((w >> 2) ^ (t & 7)) << 2) + (w & 3)] = pack_b(acc[d] * r, acc[d + 1] * r);
  }
}

__global__ void __cluster_dims__(2, 1, 1) __launch_bounds__(512, 1) fused_kernel(const __grid_constant__ Params P) {
  extern __shared__ uint8_t smem_raw[];
  const uint32_t sb = __shfl_sync(0xffffffffu, ((uint32_t)__cvta_generic_to_shared(smem_raw) + 1023) & ~1023u, 0);
  const uint32_t bar = sb + SM_BAR;
  const int wg = __shfl_sync(0xffffffffu, threadIdx.x >> 7, 0);
  const int warp = __shfl_sync(0xffffffffu, (threadIdx.x >> 5) & 3, 0);
  const int lane = threadIdx.x & 31;
  const int rank = blockIdx.x & 1;
  const int cl = blockIdx.x >> 1;
  const int ci = cl & 7;
  const int p = cl >> 3;
  const int r = 2 * ci + rank;
  const int G = 4 * ci + (p >> 1);
  const int cg = 2 * (p & 1) + rank;
  const int wcol = 56 * p - 8 * (p & 1);

  if (threadIdx.x == 0) { TSTAMP(0); GSTAMP(30); }
  unsigned tag;
  if (wg == 3) {
    asm volatile("setmaxnreg.dec.sync.aligned.u32 32;");
    auto head_x = [&](int c) {
      const uint32_t fb = bar + 8 * (B_FULLH + (c & 3));
      mbar_expect(fb, H_STAGE);
      tma_load(sb + SM_H + (c & 3) * H_STAGE, &P.xB, c * 64, r * 128, fb);
    };
    if (warp == 0) {
      if (elect()) {
        prefetch_map(&P.xB);
        prefetch_map(&P.wBh);
#pragma unroll
        for (int i = 0; i < 4; i++) mbar_init(bar + 8 * (B_FULLH + i), 1);
        asm volatile("fence.mbarrier_init.release.cluster;" ::: "memory");
        TSTAMP(11);
      }
      __syncwarp();
      asm volatile("bar.arrive 0, 512;" ::: "memory");
      if (elect()) {
        head_x(0);
#pragma unroll
        for (int b = 0; b < 6; b++)
          tma_load(sb + SM_H + 16384 + b * 4096, &P.wBh, (b >> 1) * DM + wcol, (b & 1) * 32, bar + 8 * B_FULLH);
        if (p < 3) tma_prefetch_l2(&P.xB, (4 + p) * 64, r * 128);
        tma_prefetch_l2(&P.wBh, (r % 3) * DM + wcol, 256 + (r / 3) * 32);
      }
      __syncwarp();
    } else {
      if (elect()) {
#pragma unroll
        for (int w = 1; w < 4; w++) {
          if (warp == w) {
#pragma unroll
            for (int i = 3 + w; i < B_COUNT; i += 3) {
              uint32_t c = 1;
              if ((i >= B_EMPTYH && i < B_EMPTYH + 3) || (i >= B_EMPTYKV && i < B_EMPTYKV + 4) || i == B_PUBA) c = 4;
              if (i == B_OWNRDY) c = 8;
              if (i == B_STOREDONE) c = 5;
              if (i == B_ATTNDONE || i == B_LOOPDONE || i == B_H3FREE || i == B_H1FREE) c = 2;
              mbar_init(bar + 8 * i, c);
            }
          }
        }
        asm volatile("fence.mbarrier_init.release.cluster;" ::: "memory");
      }
      __syncwarp();
      asm volatile("bar.sync 0, 512;" ::: "memory");
    }
    asm volatile("barrier.cluster.arrive.relaxed.aligned;" ::: "memory");
    asm volatile("ld.volatile.global.u32 %0, [%1];" : "=r"(tag) : "l"(P.epoch));
    if (warp == 0) {
      asm volatile("barrier.cluster.wait.acquire.aligned;" ::: "memory");
      if (elect()) {
#pragma unroll 1
        for (int c = 1; c < 7; c++) {
          if (c >= 4) mbar_wait(bar + 8 * (B_EMPTYH + c - 4), 0);
          head_x(c);
          const uint32_t st = sb + SM_H + (c & 3) * H_STAGE + 16384 + rank * 4096, fb = bar + 8 * (B_FULLH + (c & 3));
#pragma unroll
          for (int b = 0; b < 3; b++) tma_load_mc(st + b * 8192, &P.wBh, b * DM + wcol, c * 64 + rank * 32, fb);
          if (c == 3) { TSTAMP(12); prefetch_map(&P.kv); prefetch_map(&P.oB); prefetch_map(&P.outs); }
        }
      }
      __syncwarp();
      uint32_t ready = 0, todo = ~(15u << (4 * ci));
#pragma unroll 1
      for (int j = 2; j < 32; j++) {
        const int s = j & 3;
        uint32_t it = 0;
        const uint32_t want = j < 30 ? todo : 1u << (2 * (r ^ 1) + (j & 1));
        while (!(ready & want)) {
          ready = __ballot_sync(0xffffffffu, ld_flag(&P.flags[F_KV + p * 32 + lane]) == tag);
          if (++it > SPIN_LIMIT) trap_now();
        }
        const uint32_t m = ready & want, hi = m >> (2 * r) << (2 * r);
        const int blk = __ffs(hi ? hi : m) - 1;
        todo &= ~(1u << blk);
        __syncwarp();
        if (elect()) {
          if (it) fence_async_all();
          const uint32_t fb = bar + 8 * (B_FULLKV + s);
          mbar_wait(bar + 8 * (B_EMPTYKV + s), ((j - 2) >> 2) & 1);
          mbar_expect(fb, 16384);
          if (j < 30) {
            tma_load_mc(sb + SM_KV + s * 16384 + rank * 8192, &P.kv, 0, (2 * p + rank) * S_LEN + blk * 64, fb);
          } else {
            tma_load(sb + SM_KV + s * 16384, &P.kv, 0, (2 * p) * S_LEN + blk * 64, fb);
            tma_load(sb + SM_KV + s * 16384 + 8192, &P.kv, 0, (2 * p + 1) * S_LEN + blk * 64, fb);
          }
          if (j == 2) TSTAMP(9);
        }
        __syncwarp();
      }
      if (elect()) mbar_wait(bar + 8 * B_ATTNDONE, 0);
      __syncwarp();
      uint32_t left = 0xff, it = 0;
      int n = 0;
#pragma unroll 1
      while (left) {
        uint32_t m = left & __ballot_sync(0xffffffffu, lane < 8 && ld_flag(&P.flags[F_OB + (G >> 1) * 8 + lane]) == tag);
        if (++it > SPIN_LIMIT) trap_now();
        left &= ~m;
        if (m && elect()) {
          fence_async_all();
#pragma unroll 1
          for (int k = n; m; k++, m &= m - 1) {
            const int c = __ffs(m) - 1;
            asm volatile("st.shared.u32 [%0], %1;" ::"r"(sb + SM_ORDER + 4 * k), "r"(c < 7 ? c * 448 : 3072) : "memory");
            mbar_expect(bar + 8 * (B_FULLOB + k), 8192);
            tma_load(sb + SM_KV + k * 8192, &P.oB, c * 64, G * 64, bar + 8 * (B_FULLOB + k));
            if (k == 7) TSTAMP(10);
          }
        }
        __syncwarp();
        n = 8 - __popc(left);
      }
    } else if (warp == 1) {
      if (A_ON && elect()) {
        prefetch_map(&P.xA);
        prefetch_map(&P.wA);
        mbar_wait(bar + 8 * (B_EMPTYH + 1), 0);
        if (tag == 0) trap_now();
        if (p < 7) tma_prefetch_l2(&P.xA, p * 64, r * 128);
#pragma unroll 1
        for (int b = 0; b < 3; b++) tma_prefetch_l2(&P.wA, (2 - b) * DM + wcol, (r % 7) * 64);
        prefetch_map(&P.woA);
        prefetch_map(&P.woB);
        prefetch_map(&P.oA);
        mbar_wait(bar + 8 * B_H3FREE, 0);
        mbar_wait(bar + 8 * (B_FULLH + 2), 1);
        int c = 6, col = 2 * DM + wcol;
#pragma unroll 1
        for (int n = 0; n < 21; n++) {
          const int s = n & 3;
          if (n < 7) {
            if (n == 1 && AEARLY) mbar_wait(bar + 8 * B_H1FREE, 0);
            if (n == 1 + AEARLY) mbar_wait(bar + 8 * (B_FULLKV + AWAIT), 0);
            if (n > AEARLY + AFLY) mbar_wait(bar + 8 * (B_FULLXA + n - 1 - AFLY), 0);
            mbar_expect(bar + 8 * (B_FULLXA + c), 16384);
            tma_load(sb + SM_XA + c * 16384, &P.xA, c * 64, r * 128, bar + 8 * (B_FULLXA + c));
          }
          if (n >= 4) mbar_wait(bar + 8 * (B_EMPTYWA + s), ((n >> 2) - 1) & 1);
          mbar_expect(bar + 8 * (B_FULLWA + s), 8192);
          tma_load(sb + SM_WA + s * 8192, &P.wA, col, c * 64, bar + 8 * (B_FULLWA + s));
          if (++c == 7) c = 0;
          if (c == 6) col -= DM;
        }
        mbar_wait(bar + 8 * B_XAFREE, 0);
#pragma unroll 1
        for (int n = 0; n < 7; n++) {
          const uint32_t fb = bar + 8 * (B_FULLXA + n);
          if (n >= 2) mbar_wait(fb - 16, 1);
          mbar_expect(fb, 16384);
          tma_load(sb + SM_XA + n * 8192, &P.woA, cg * 112, n * 64, fb);
          tma_load(sb + SM_XA + 57344 + n * 8192, &P.woA, cg * 112 + 64, n * 64, fb);
        }
      }
      __syncwarp();
      uint32_t left = A_ON ? 0xff : 0, it = 0;
      int n = 21;
#pragma unroll 1
      while (left) {
        uint32_t m = left & __ballot_sync(0xffffffffu, lane < 8 && ld_flag(&P.flags[F_OA + (G >> 1) * 8 + lane]) == tag);
        if (++it > SPIN_LIMIT) trap_now();
        left &= ~m;
        if (!m) { __nanosleep(200); continue; }
        if (elect()) {
          fence_async_all();
#pragma unroll 1
          for (int k = n; m; k++, m &= m - 1) {
            const int c = __ffs(m) - 1, s = k & 3;
            mbar_wait(bar + 8 * (B_EMPTYWA + s), ((k >> 2) - 1) & 1);
            asm volatile("st.shared.u32 [%0], %1;" ::"r"(sb + SM_ORDER + 32 + 4 * (k - 21)), "r"(c) : "memory");
            mbar_expect(bar + 8 * (B_FULLWA + s), 8192);
            tma_load(sb + SM_WA + s * 8192, &P.oA, c * 64, G * 64, bar + 8 * (B_FULLWA + s));
          }
        }
        __syncwarp();
        n = 29 - __popc(left);
      }
    } else if (warp == 2) {
      if (elect()) {
        mbar_wait(bar + 8 * B_OWNRDY, 0);
        TSTAMP(15);
#pragma unroll 1
        for (int h = 0; h < 2; h++) {
          tma_store(&P.kv, 0, (2 * p) * S_LEN + r * 128 + h * 64, sb + SM_KV + h * 16384);
          tma_store(&P.kv, 0, (2 * p + 1) * S_LEN + r * 128 + h * 64, sb + SM_KV + h * 16384 + 8192);
          bulk_commit();
          bulk_wait();
          mbar_arrive(bar + 8 * (B_STOREDONE + h));
          st_release(&P.flags[F_KV + p * 32 + 2 * r + h], tag);
          if (h == 0) TSTAMP(14); else TSTAMP(8);
        }
        if (A_ON) {
          mbar_wait(bar + 8 * B_PUBA, 0);
          tma_store(&P.oA, 64 * p, r * 128, sb + SM_STG);
          tma_store(&P.oA, 64 * p, r * 128 + 64, sb + SM_STG + 8192);
          bulk_commit();
          bulk_wait();
        }
        mbar_arrive(bar + 8 * B_STGFREE);
        if (A_ON) st_release(&P.flags[F_OA + r * 8 + p], tag);
        TSTAMP(20);
        mbar_wait(bar + 8 * B_ATTNDONE, 0);
        tma_store(&P.oB, 64 * p, r * 128, sb + SM_STG);
        tma_store(&P.oB, 64 * p, r * 128 + 64, sb + SM_STG + 8192);
        bulk_commit();
        bulk_wait();
        TSTAMP(13);
        mbar_arrive(bar + 8 * B_STGFREE);
        st_release(&P.flags[F_OB + r * 8 + p], tag);
        TSTAMP(5);
      }
      __syncwarp();
    } else {
      uint32_t kn = 0, vm = 0, it = 0;
#pragma unroll 1
      for (int u = 0; u < 2; u++) {
        const unsigned long long* src = P.stats + (size_t)(p * 64 + lane * 2 + u) * 2;
        unsigned long long a, b;
        while (true) {
          asm volatile("ld.relaxed.gpu.global.u64 %0, [%1];" : "=l"(a) : "l"(src) : "memory");
          asm volatile("ld.relaxed.gpu.global.u64 %0, [%1];" : "=l"(b) : "l"(src + 1) : "memory");
          if ((unsigned)(a >> 32) == tag && (unsigned)(b >> 32) == tag) break;
          if (++it > SPIN_LIMIT) trap_now();
          __nanosleep(500);
        }
        kn = __vmaxu2(kn, (uint32_t)a);
        vm = __vmaxu2(vm, (uint32_t)b);
      }
#pragma unroll 1
      for (int o = 16; o; o >>= 1) {
        kn = __vmaxu2(kn, __shfl_xor_sync(0xffffffffu, kn, o));
        vm = __vmaxu2(vm, __shfl_xor_sync(0xffffffffu, vm, o));
      }
      if (elect()) {
        asm volatile("st.shared.v2.u32 [%0], {%1, %2};" ::"r"(sb + SM_STAT), "r"(kn), "r"(vm) : "memory");
        mbar_arrive(bar + 8 * B_STATS);
        mbar_expect(bar + 8 * B_FULLWOB, 7 * 16384);
#pragma unroll 1
        for (int c = 0; c < 7; c++) {
          mbar_wait(bar + 8 * (B_EMPTYXA + c), 0);
          tma_load(sb + SM_XA + c * 8192, &P.woB, cg * 112, c * 64, bar + 8 * B_FULLWOB);
          tma_load(sb + SM_XA + 57344 + c * 8192, &P.woB, cg * 112 + 48, c * 64, bar + 8 * B_FULLWOB);
        }
      }
      __syncwarp();
    }
  } else if (wg < 2) {
    if (OHALF && threadIdx.x < 96) {
      const int w = threadIdx.x & 31, row = w >> 2, col = (w & 3) * 2;
      const uint32_t v = (threadIdx.x >> 5) == 1 ? 0u : (row == col ? 0x00003c00u : (row == col + 1 ? 0x3c000000u : 0u));
      asm volatile("st.shared.u32 [%0], %1;" ::"r"(sb + SM_EYE + 4 * threadIdx.x), "r"(v) : "memory");
      fence_async_smem();
    }
    asm volatile("bar.sync 0, 512;" ::: "memory");
    asm volatile("barrier.cluster.arrive.relaxed.aligned;" ::: "memory");
    asm volatile("ld.volatile.global.u32 %0, [%1];" : "=r"(tag) : "l"(P.epoch));
    asm volatile("setmaxnreg.inc.sync.aligned.u32 168;");
    const int t = threadIdx.x & 127, g = lane >> 2, c4 = lane & 3;
    uint32_t qA[8], qB[8];
    const uint32_t empty_l = bar + 8 * B_EMPTYKV, empty_r = mapa(empty_l, rank ^ 1);
    asm volatile("barrier.cluster.wait.acquire.aligned;" ::: "memory");
    {
      float acc[96];
      const uint32_t xd = desc_lo(sb + SM_H + wg * 8192, 16), wd = desc_lo(sb + SM_H + 16384, 8192) + (p & 1);
#pragma unroll 1
      for (int c = 0; c < 7; c++) {
        const uint32_t so = (c & 3) * (H_STAGE >> 4);
        mbar_wait(bar + 8 * (B_FULLH + (c & 3)), c >> 2);
        if (threadIdx.x == 0) TSTAMP(c ? 21 + c : 1);
        wg_fence();
#pragma unroll
        for (int kk = 0; kk < 4; kk++) mma_n192_ss_tb(acc, desc(xd + so + kk * 2), desc(wd + so + kk * 128), kk ? 1 : c);
        wg_commit();
        wg_wait<1>();
        if (c == 1 && tag == 0) trap_now();
        const bool rel = c > 0 && c < 4;
        mbar_arrive_if(bar + 8 * (B_EMPTYH - 1) + 8 * c, t == 0 && rel);
        mbar_arrive_cluster_if(empty_r - 8 * (B_EMPTYKV - B_EMPTYH + 1) + 8 * c, t == 32 && rel);
        mbar_arrive_if(bar + 8 * B_H3FREE, t == 64 && c == 4);
        mbar_arrive_if(bar + 8 * B_H1FREE, t == 96 && c == 6);
      }
      wg_wait<0>();
      pin(acc);
      if (threadIdx.x == 0) TSTAMP(2);
      mbar_arrive_if(empty_l + 16, t == 0);
      mbar_arrive_if(empty_l + 24, t == 0);
      mbar_arrive_cluster_if(empty_r + 16, t == 32);
      mbar_arrive_cluster_if(empty_r + 24, t == 32);
      const bool lo = c4 < 2;
      const int mrow = (lane & 7) + ((lane >> 3) & 1) * 8 + warp * 16;
      const uint32_t tile = sb + SM_KV + wg * 16384 + mrow * 128;
#pragma unroll
      for (int h = 0; h < 2; h++) {
#pragma unroll
        for (int ch = 0; ch < 8; ch += 2) {
          uint32_t v[4];
#pragma unroll
          for (int i = 0; i < 4; i++) {
            const int cc = ch + (i >> 1);
            const int b = (cc & 3) + 3 * h;
            const int a = 32 + (cc >> 2) * 32 + 4 * b + 2 * (i & 1);
            v[i] = pack_h(acc[a], acc[a + 1]);
            if (b == 3) {
              const uint32_t fill = (cc >= 4 && c4 == (h ? 0 : 2)) ? 0x00003c00u : 0u;
              v[i] = (lo == (h == 0)) ? v[i] : fill;
            }
          }
          stsm4(tile + h * 8192 + (((ch + (lane >> 4)) ^ (mrow & 7)) << 4), v[0], v[1], v[2], v[3]);
        }
      }
      fence_async_smem();
      __syncwarp();
      mbar_arrive_if(bar + 8 * B_OWNRDY, lane == 0);
#pragma unroll
      for (int i = 0; i < 8; i++) {
        const int a = 4 * (i >> 1) + 2 * (i & 1);
        qA[i] = pack_h(acc[a] * QSCALE, acc[a + 1] * QSCALE);
        qB[i] = pack_h(acc[12 + a] * QSCALE, acc[13 + a] * QSCALE);
      }
      if (!lo) qA[6] = qA[7] = 0;
      if (lo) qB[0] = qB[1] = 0;
    }
    float qn[2];
#pragma unroll
    for (int h = 0; h < 2; h++) {
      const uint32_t (&q)[8] = h ? qB : qA;
      uint32_t n0 = 0, n1 = 0;
#pragma unroll
      for (int i = 0; i < 4; i++) { n0 = hfma2(q[2 * i], q[2 * i], n0); n1 = hfma2(q[2 * i + 1], q[2 * i + 1], n1); }
      float a = h_lo(n0) + h_hi(n0), b = h_lo(n1) + h_hi(n1);
      a += __shfl_xor_sync(0xffffffffu, a, 1);
      b += __shfl_xor_sync(0xffffffffu, b, 1);
      a += __shfl_xor_sync(0xffffffffu, a, 2);
      b += __shfl_xor_sync(0xffffffffu, b, 2);
      qn[h] = __uint_as_float(max(__float_as_uint(a), __float_as_uint(b)));
    }
    mbar_wait(bar + 8 * B_OWNRDY, 0);
    if (threadIdx.x == 0) TSTAMP(3);

    float oA[16], oB[16];
    uint32_t sA[16], sB[16], pA[16], pB[16];
    uint32_t k0 = desc_lo(sb + SM_KV, 16), v0;
    const uint32_t zero = P.zero;
    uint32_t chain = 0x3c003c00u;
    uint32_t hA[8], hB[8];
    const uint64_t eye = (uint64_t)8 << 32 | desc_lo(sb + SM_EYE, 128);
    auto pv1 = [&](float (&o)[16], uint32_t (&h)[8], const uint32_t (&pp)[16], int kk, uint32_t vd, int acc) {
      if (OHALF) mma_pv_h(h, pp[4 * kk], pp[4 * kk + 1], pp[4 * kk + 2], pp[4 * kk + 3], desc(vd + kk * 128), acc);
      else mma_pv(o, pp[4 * kk], pp[4 * kk + 1], pp[4 * kk + 2], pp[4 * kk + 3], desc(vd + kk * 128), 1);
    };
    auto flush = [&](float (&o)[16], const uint32_t (&h)[8]) {
      if (OHALF) {
        mma_fl(*reinterpret_cast<float (*)[8]>(&o[0]), h[0], h[1], h[2], h[3], eye, 1);
        mma_fl(*reinterpret_cast<float (*)[8]>(&o[8]), h[4], h[5], h[6], h[7], eye, 1);
      }
    };
    auto pv_qk = [&](float (&o)[16], uint32_t (&h)[8], int acc, const uint32_t (&pp)[16], uint32_t vd, uint32_t (&s)[16],
                     const uint32_t (&q)[8], uint32_t kd) {
      if (WORD == 0) {
        pv1(o, h, pp, 0, vd, acc);
        mma_qk(s, q[0], q[1], q[2], q[3], desc(kd), 0);
        pv1(o, h, pp, 1, vd, 1);
        mma_qk(s, q[4], q[5], q[6], q[7], desc(kd + 2), 1);
        pv1(o, h, pp, 2, vd, 1);
        pv1(o, h, pp, 3, vd, 1);
      } else if (WORD == 1) {
        pv1(o, h, pp, 0, vd, acc);
        pv1(o, h, pp, 1, vd, 1);
        mma_qk(s, q[0], q[1], q[2], q[3], desc(kd), 0);
        pv1(o, h, pp, 2, vd, 1);
        mma_qk(s, q[4], q[5], q[6], q[7], desc(kd + 2), 1);
        pv1(o, h, pp, 3, vd, 1);
      } else {
        mma_qk(s, q[0], q[1], q[2], q[3], desc(kd), 0);
        pv1(o, h, pp, 0, vd, acc);
        pv1(o, h, pp, 1, vd, 1);
        mma_qk(s, q[4], q[5], q[6], q[7], desc(kd + 2), 1);
        pv1(o, h, pp, 2, vd, 1);
        pv1(o, h, pp, 3, vd, 1);
      }
    };
#pragma unroll
    for (int i = 0; i < 16; i++) { oA[i] = oB[i] = 0.f; pB[i] = 0; hA[i >> 1] = hB[i >> 1] = 0; }
    pin(qA); pin(qB); pin(oA); pin(oB); pin(hA); pin(hB);
    wg_fence();
    mma_qk(sA, qA[0], qA[1], qA[2], qA[3], desc(k0), 0);
    mma_qk(sA, qA[4], qA[5], qA[6], qA[7], desc(k0 + 2), 1);
    wg_commit();
    wg_wait<0>();
    pin(sA);
    if (WOFF && wg == 1) { const long long c0 = clock64(); while (clock64() - c0 < WOFF) {} }
#pragma unroll 1
    for (int o = 0; o < 8; o++) {
      k0 = __shfl_sync(0xffffffffu, k0, 0);
      v0 = k0 + 4;
#pragma unroll
      for (int u = 0; u < 4; u++) {
        const uint32_t so = u * 1024, sp = ((u + 3) & 3) * 1024, sn = ((u + 1) & 3) * 1024;
        const uint32_t fbar = bar + 8 * (B_FULLKV + ((u + 1) & 3)), par = (u == 0 ? o + 1 : o) & 1;
        const bool nowait = (u == 0 && o == 0) || (u == 3 && o == 7);
        const uint32_t have = mbar_test(fbar, par) | nowait;
        pin(pB);
        wg_fence();
        pv_qk(oB, hB, u != 1, pB, v0 + 512 + (u == 0 && o == 0 ? 0 : sp), sB, qB, k0 + so + 512);
        if (u == 0) flush(oA, hA);
        wg_commit();
        if (BBK & 1) mbar_wait(fbar, par, zero + 1);
        exp_tile(sA, pA, zero, chain);
        pin(pA);
        wg_wait<0>();
        pin(sB); pin(oB); pin(sA); pin(hB); pin(oA);
        if (u == 1 || u == 2) mbar_wait(bar + 8 * (B_STOREDONE + u - 1), 0, o);
        mbar_wait(fbar, par, have);
        const bool rel = u == 0 ? o > 0 : (o < 7);
        mbar_arrive_if(empty_l + (sp >> 7), t == 0 && rel);
        mbar_arrive_cluster_if(empty_r + (sp >> 7), t == 32 && rel);
        wg_fence();
        pv_qk(oA, hA, u != 0, pA, v0 + so, sA, qA, k0 + sn);
        if (u == 0) flush(oB, hB);
        wg_commit();
        if (BBK & 2) mbar_wait(fbar, par, zero + 1);
        exp_tile(sB, pB, zero, chain);
        pin(pB);
        wg_wait<0>();
        pin(sA); pin(oA); pin(sB); pin(hA); pin(oB);
      }
    }
    wg_fence();
#pragma unroll
    for (int kk = 0; kk < 4; kk++) pv1(oB, hB, pB, kk, v0 + 3 * 1024 + 512, 1);
    flush(oA, hA);
    wg_commit();
    if (OHALF) {
      wg_wait<0>();
      pin(hB); pin(oA);
      wg_fence();
      flush(oB, hB);
      wg_commit();
    }
    if (threadIdx.x == 0) TSTAMP(29);
    mbar_wait(bar + 8 * B_STATS, 0);
    mbar_wait(bar + 8 * B_STGFREE, 0);
    uint32_t kn, vm;
    asm volatile("ld.shared.v2.u32 {%0, %1}, [%2];" : "=r"(kn), "=r"(vm) : "r"(sb + SM_STAT));
    bool ok = qn[0] * h_lo(kn) <= 1024.f && qn[1] * h_hi(kn) <= 1024.f && qn[0] <= 65504.f && qn[1] <= 65504.f &&
              h_lo(kn) <= 65504.f && h_hi(kn) <= 65504.f && h_lo(vm) <= 65504.f && h_hi(vm) <= 65504.f &&
              h_lo(vm) >= 0x1p-10f && h_hi(vm) >= 0x1p-10f && !P.force_slow;
    wg_wait<0>();
    pin(oB); pin(oA);
    if (threadIdx.x == 0) TSTAMP(4);
    mbar_arrive_if(bar + 8 * B_LOOPDONE, t == 0);
    {
      uint32_t v[14];
#pragma unroll
      for (int hr = 0; hr < 2; hr++) {
        const float lA = __shfl_sync(0xffffffffu, oA[12 + 2 * hr], (lane & ~3) | 2);
        const float lB = __shfl_sync(0xffffffffu, oB[2 * hr], lane & ~3);
        ok = ok && lA >= 128.f && lA < 16384.f && lB >= 128.f && lB < 16384.f &&
             (!OHALF || (lA * h_lo(vm) <= 60000.f && lB * h_hi(vm) <= 60000.f));
        const float iA = rcp_f(lA), iB = rcp_f(lB);
#pragma unroll
        for (int b = 0; b < 7; b++) {
          float a0, a1;
          if (b < 3) { a0 = oA[4 * b + 2 * hr] * iA; a1 = oA[4 * b + 2 * hr + 1] * iA; }
          else if (b > 3) { a0 = oB[4 * (b - 3) + 2 * hr] * iB; a1 = oB[4 * (b - 3) + 2 * hr + 1] * iB; }
          else if (c4 < 2) { a0 = oA[12 + 2 * hr] * iA; a1 = oA[13 + 2 * hr] * iA; }
          else { a0 = oB[2 * hr] * iB; a1 = oB[2 * hr + 1] * iB; }
          v[2 * b + hr] = pack_b(a0, a1);
        }
      }
      stage64(sb + SM_STG + wg * 8192 + warp * 2048, v, lane, p == 7);
      fence_async_smem();
    }
    if (__builtin_expect(named_or(2 + wg, 128, !ok), 0)) {
      mbar_wait(bar + 8 * B_LOOPDONE, 0);
      uint8_t* base = smem_raw + (sb - (uint32_t)__cvta_generic_to_shared(smem_raw));
      slow_attention(P.xBp, P.wBp, reinterpret_cast<float*>(base + SM_KV + wg * 32768),
                     reinterpret_cast<uint32_t*>(base + SM_STG + wg * 8192), r * 128 + wg * 64, p, t, 2 + wg);
      fence_async_smem();
      named_sync(2 + wg, 128);
    }
    if (threadIdx.x == 0) TSTAMP(28);
    mbar_arrive_if(bar + 8 * B_ATTNDONE, t == 0);
    {
      float o[28];
      const uint32_t od = desc_lo(sb + SM_KV, 16), wo = desc_lo(sb + SM_XA + wg * (57344 + 16), 16);
      mbar_wait(bar + 8 * B_FULLWOB, 0);
#pragma unroll 1
      for (int n = 0; n < 8; n++) {
        mbar_wait(bar + 8 * (B_FULLOB + n), 0);
        uint32_t c;
        asm volatile("ld.shared.u32 %0, [%1];" : "=r"(c) : "r"(sb + SM_ORDER + 4 * n) : "memory");
        const uint32_t wc = wo + __shfl_sync(0xffffffffu, c, 0);
        if (n == 0 && threadIdx.x == 0) TSTAMP(6);
        wg_fence();
#pragma unroll
        for (int kk = 0; kk < 4; kk++) mma_n56_ss_tb(o, desc(od + n * 512 + kk * 2), desc(wc + kk * 128), kk ? 1 : n);
        wg_commit();
      }
      wg_wait<0>();
      pin(o);
      uint32_t v[14];
#pragma unroll
      for (int i = 0; i < 14; i++) v[i] = pack_b(o[2 * i], o[2 * i + 1]);
      mbar_wait(bar + 8 * B_STGFREE, 1);
      stage56(sb + SM_STG + wg * 8192 + warp * (16 * 112), v, lane);
      fence_async_smem();
      named_sync(2 + wg, 128);
      if (t == 0) {
        tma_store(&P.outs, DM + cg * 112 + wg * 56, G * 64, sb + SM_STG + wg * 8192);
        bulk_commit();
        asm volatile("cp.async.bulk.wait_group 0;" ::: "memory");
      }
    }
    if (threadIdx.x == 0) { TSTAMP(7); GSTAMP(31); }
    if (blockIdx.x == 0 && threadIdx.x == 0) *(volatile unsigned*)P.epoch = tag + 1 ? tag + 1 : 1;
    if (threadIdx.x == 0) TDUMP();
  } else {
    asm volatile("bar.sync 0, 512;" ::: "memory");
    asm volatile("barrier.cluster.arrive.relaxed.aligned;" ::: "memory");
    asm volatile("ld.volatile.global.u32 %0, [%1];" : "=r"(tag) : "l"(P.epoch));
    asm volatile("setmaxnreg.inc.sync.aligned.u32 144;");
    const int t = threadIdx.x & 127, g = lane >> 2, c4 = lane & 3;
    auto kv_stats = [&]() {
    mbar_wait(bar + 8 * B_OWNRDY, 0);
    {
      uint32_t sk = 0, sv = 0;
#pragma unroll 1
      for (int h = 0; h < 2; h++) {
        const uint32_t rowa = sb + SM_KV + (t >> 6) * 16384 + h * 8192 + (t & 63) * 128;
        uint32_t n2 = 0, vm = 0;
#pragma unroll
        for (int ch = 0; ch < 8; ch++) {
          uint32_t v[4];
          asm volatile("ld.shared.v4.u32 {%0, %1, %2, %3}, [%4];" : "=r"(v[0]), "=r"(v[1]), "=r"(v[2]), "=r"(v[3])
                       : "r"(rowa + ((ch ^ (t & 7)) << 4)));
          if (ch == 7 && h == 0) v[2] = 0;
          if (ch == 4 && h == 1) v[0] = 0;
#pragma unroll
          for (int i = 0; i < 4; i++) {
            if (ch < 4) n2 = hfma2(v[i], v[i], n2);
            else vm = habsmax2(vm, v[i]);
          }
        }
        const uint32_t ns = __half_as_ushort(__float2half_rn(h_lo(n2) + h_hi(n2)));
        sk |= __reduce_max_sync(0xffffffffu, ns) << (16 * h);
        sv |= __reduce_max_sync(0xffffffffu, max(vm & 0xffffu, vm >> 16)) << (16 * h);
      }
      if (lane == 0) {
        mbar_arrive(bar + 8 * B_STOREDONE);
        unsigned long long* dst = P.stats + (size_t)(p * 64 + r * 4 + warp) * 2;
        const unsigned long long hi = (unsigned long long)tag << 32;
        asm volatile("st.relaxed.gpu.global.u64 [%0], %1;" ::"l"(dst), "l"(hi | sk) : "memory");
        asm volatile("st.relaxed.gpu.global.u64 [%0], %1;" ::"l"(dst + 1), "l"(hi | sv) : "memory");
      }
    }
      if (t == 0) TSTAMP(16);
    };
    if (!A_ON) {
      kv_stats();
      mbar_wait(bar + 8 * (B_FULLKV + 3), 0);
      if (t == 0) for (int c = 0; c < 7; c++) mbar_arrive(bar + 8 * (B_EMPTYXA + c));
    } else {
    const uint32_t xa = desc_lo(sb + SM_XA, 16), oa = desc_lo(sb + SM_WA, 16), wa = oa + (p & 1);
    {
      float acc[64];
#pragma unroll 1
      for (int n = 0; n < 14; n++) {
        const int c = (n == 0 || n == 7) ? 6 : (n < 7 ? n - 1 : n - 8);
        if (t == 0) ISTAMP(8 + n, clock());
        mbar_wait(bar + 8 * (B_FULLXA + c), 0, n >= 7);
        mbar_wait(bar + 8 * (B_FULLWA + (n & 3)), (n >> 2) & 1);
        if (t == 0) ISTAMP(72 + n, clock());
#pragma unroll
        for (int kk = 0; kk < 4; kk++) {
          if (kk % AGRP == 0) wg_fence();
          mma_n128_ss_ta(acc, desc(wa + (n & 3) * 512 + kk * 128), desc(xa + c * 1024 + kk * 2), kk ? 1 : c != 6);
          if (kk % AGRP == AGRP - 1) { wg_commit(); wg_wait<0>(); }
        }
        mbar_arrive_if(bar + 8 * (B_EMPTYWA + (n & 3)), t == 0);
        if (n == 0) kv_stats();
        if (n == 6) {
          pin(acc);
          const int mrow = (lane & 7) + ((lane >> 3) & 1) * 8 + warp * 16;
          const uint32_t one = g == 0 ? 0x3f803f80u : 0u;
#pragma unroll
          for (int b = 0; b < 16; b += 2) {
            const int ch = (b & 7) + (lane >> 4);
            const uint32_t hi0 = pack_b(acc[4 * b + 2], acc[4 * b + 3]), hi1 = pack_b(acc[4 * b + 6], acc[4 * b + 7]);
            stsm4(sb + SM_STG + (b >> 3) * 8192 + mrow * 128 + ((ch ^ (mrow & 7)) << 4), pack_b(acc[4 * b], acc[4 * b + 1]),
                  warp == 3 ? one : hi0, pack_b(acc[4 * b + 4], acc[4 * b + 5]), warp == 3 ? one : hi1);
          }
          fence_async_smem();
          named_sync(1, 128);
        }
      }
      pin(acc);
      uint32_t pk[32];
#pragma unroll
      for (int i = 0; i < 32; i++) pk[i] = phi2(acc[2 * i], acc[2 * i + 1]);
      float kv[32];
      const uint32_t vt = desc_lo(sb + SM_STG, 16);
      pin(pk);
      if (t == 0) ISTAMP(96 + 15, clock());
#pragma unroll
      for (int kk = 0; kk < 8; kk++) {
        if (!(kk & 3)) wg_fence();
        mma_n64_rs(kv, pk[4 * kk], pk[4 * kk + 1], pk[4 * kk + 2], pk[4 * kk + 3], desc(vt + (kk >> 2) * 512 + (kk & 3) * 2), kk);
        if ((kk & 3) == 3) { wg_commit(); wg_wait<0>(); }
      }
      pin(kv);
      if (t == 0) ISTAMP(96 + 22, clock());
#pragma unroll
      for (int hr = 0; hr < 2; hr++) {
        const int dk = warp * 16 + hr * 8 + g;
        uint4* dst = P.part + (size_t)((p * 16 + r) * 56 + dk) * 32 + c4;
#pragma unroll
        for (int b = 0; b < 8; b++) {
          const int cp = 4 * b + c4;
          if (dk < 56 && (cp == 28 || (cp < 28 && (cp >= 14) == (dk >= DH))))
            asm volatile("st.relaxed.gpu.global.v4.u32 [%0], {%1, %2, %3, %3};" ::"l"(dst + 4 * b),
                         "r"(__float_as_uint(kv[4 * b + 2 * hr])), "r"(__float_as_uint(kv[4 * b + 2 * hr + 1])), "r"(tag) : "memory");
        }
      }
    }
    if (t == 0) TSTAMP(17);
    float q[2][32];
    const int dk = r * 4 + warp;
    const bool red_on = dk < 56 && (lane == 28 || (lane < 28 && (lane >= 14) == (dk >= DH)));
    const uint4* red_src = P.part + (size_t)(p * 16 * 56 + dk) * 32 + lane;
    uint4 v[8];
    float ra = 0.f, rb = 0.f;
    auto load8 = [&](const uint4* src, int stride) {
#pragma unroll
      for (int i = 0; i < 8; i++)
        asm volatile("ld.relaxed.gpu.global.v4.u32 {%0, %1, %2, %3}, [%4];" : "=r"(v[i].x), "=r"(v[i].y), "=r"(v[i].z), "=r"(v[i].w)
                     : "l"(src + (size_t)i * stride) : "memory");
    };
#pragma unroll 1
    for (int i = 0; i < 7; i++) {
      const int n = 14 + i, c = i ? i - 1 : 6;
      if (t == 0) ISTAMP(8 + n, clock());
      mbar_wait(bar + 8 * (B_FULLWA + (n & 3)), (n >> 2) & 1);
      if (t == 0) ISTAMP(72 + n, clock());
      if (i == 2 && red_on) load8(red_src, 56 * 32);
#pragma unroll
      for (int kk = 0; kk < 4; kk++) {
        const uint64_t bd = desc(wa + (n & 3) * 512 + kk * 128);
        if (kk % AGRP == 0) wg_fence();
        mma_n64_ss_tb(q[0], desc(xa + c * 1024 + kk * 2), bd, kk ? 1 : i);
        mma_n64_ss_tb(q[1], desc(xa + c * 1024 + 512 + kk * 2), bd, kk ? 1 : i);
        if (kk % AGRP == AGRP - 1) { wg_commit(); wg_wait<0>(); }
      }
      mbar_arrive_if(bar + 8 * (B_EMPTYWA + (n & 3)), t == 0);
      if (i == 3 || i == 5) {
        if (red_on) {
          uint32_t it = 0;
          while (true) {
            bool ok = true;
#pragma unroll
            for (int k = 0; k < 8; k++) ok = ok && v[k].z == tag;
            if (ok) break;
            if (++it > SPIN_LIMIT) trap_now();
            __nanosleep(300);
            load8(red_src, 56 * 32);
          }
#pragma unroll
          for (int k = 0; k < 8; k++) { ra += __uint_as_float(v[k].x); rb += __uint_as_float(v[k].y); }
          red_src += 8 * 56 * 32;
          if (i == 3) load8(red_src, 56 * 32);
        }
        __syncwarp();
        if (i == 5) {
          if (lane == 28) { if (dk >= DH) { rb = ra; ra = 0.f; } else rb = 0.f; }
          asm volatile("st.relaxed.gpu.global.v2.u32 [%0], {%1, %2};" ::"l"(P.kvf + (size_t)(p * 64 + dk) * 32 + lane),
                       "r"(pack_b(ra, rb)), "r"(tag) : "memory");
          if (t == 0) TSTAMP(21);
        }
      }
    }
    pin(q[0]);
    pin(q[1]);
    mbar_arrive_if(bar + 8 * B_XAFREE, t == 0);
    if (t == 0) ISTAMP(96 + 16, clock());
    uint32_t pq[2][16];
#pragma unroll
    for (int i = 0; i < 14; i++) pq[0][i] = phi2(q[0][2 * i], q[0][2 * i + 1]);
    const uint4* gsrc = reinterpret_cast<const uint4*>(P.kvf + (size_t)(p * 64 + warp * 16) * 32) + lane;
    if (t == 0) ISTAMP(96 + 17, clock());
    load8(gsrc, 32);
#pragma unroll
    for (int i = 0; i < 14; i++) pq[1][i] = phi2(q[1][2 * i], q[1][2 * i + 1]);
    pq[0][14] = pq[0][15] = pq[1][14] = pq[1][15] = 0;
    pin(pq[1]);
    if (t == 0) ISTAMP(96 + 18, clock());
    {
      uint32_t it = 0;
      while (true) {
        bool ok = true;
#pragma unroll
        for (int i = 0; i < 8; i++) ok = ok && v[i].y == tag && v[i].w == tag;
        if (ok) break;
        if (++it > SPIN_LIMIT) trap_now();
        __nanosleep(300);
        load8(gsrc, 32);
      }
      __syncwarp();
      if (t == 0) { ISTAMP(96 + 19, clock()); ISTAMP(96 + 23, it); }
#pragma unroll
      for (int i = 0; i < 8; i++) {
        const int row = warp * 16 + 2 * i + (lane >> 4);
        asm volatile("st.shared.v2.u32 [%0], {%1, %2};" ::"r"(sb + SM_STG + row * 128 + ((((lane & 15) >> 1) ^ (row & 7)) << 4) + (lane & 1) * 8),
                     "r"(v[i].x), "r"(v[i].z) : "memory");
      }
      fence_async_smem();
      named_sync(1, 128);
    }
    if (t == 0) ISTAMP(96 + 20, clock());
    {
      const uint32_t kd = desc_lo(sb + SM_STG, 16);
      pin(pq[0]);
      pin(pq[1]);
#pragma unroll
      for (int kk = 0; kk < 4; kk++) {
        if (!(kk & 1)) wg_fence();
        mma_n64_rs_tb(q[0], pq[0][4 * kk], pq[0][4 * kk + 1], pq[0][4 * kk + 2], pq[0][4 * kk + 3], desc(kd + kk * 128), kk);
        mma_n64_rs_tb(q[1], pq[1][4 * kk], pq[1][4 * kk + 1], pq[1][4 * kk + 2], pq[1][4 * kk + 3], desc(kd + kk * 128), kk);
        if (kk & 1) { wg_commit(); wg_wait<0>(); }
      }
      pin(q[0]);
      pin(q[1]);
      if (t == 0) ISTAMP(96 + 21, clock());
#pragma unroll
      for (int m = 0; m < 2; m++) {
        uint32_t v[14];
#pragma unroll
        for (int hr = 0; hr < 2; hr++) {
          const float i0 = rcp_f(__shfl_sync(0xffffffffu, q[m][28 + 2 * hr], lane & ~3) + 1e-6f);
          const float i1 = rcp_f(__shfl_sync(0xffffffffu, q[m][29 + 2 * hr], lane & ~3) + 1e-6f);
#pragma unroll
          for (int b = 0; b < 7; b++) {
            const float inv = b < 3 ? i0 : (b > 3 ? i1 : (c4 < 2 ? i0 : i1));
            v[2 * b + hr] = pack_b(q[m][4 * b + 2 * hr] * inv, q[m][4 * b + 2 * hr + 1] * inv);
          }
        }
        stage64(sb + SM_STG + m * 8192 + warp * 2048, v, lane, p == 7);
      }
      fence_async_smem();
      __syncwarp();
      mbar_arrive_if(bar + 8 * B_PUBA, lane == 0);
    }
    if (t == 0) TSTAMP(18);
    {
      float o[56];
      const uint32_t wo = desc_lo(sb + SM_XA, 57344);
#pragma unroll 1
      for (int i = 0; i < 7; i++) mbar_wait(bar + 8 * (B_FULLXA + i), 1);
      uint32_t done = 0;
#pragma unroll 1
      for (int i = 0; i < 8; i++) {
        const int n = 21 + i;
        if (t == 0 && i < 7) ISTAMP(56 + i, clock());
        mbar_wait(bar + 8 * (B_FULLWA + (n & 3)), (n >> 2) & 1);
        if (t == 0 && i < 7) ISTAMP(120 + i, clock());
        uint32_t c;
        asm volatile("ld.shared.u32 %0, [%1];" : "=r"(c) : "r"(sb + SM_ORDER + 32 + 4 * i) : "memory");
        c = __shfl_sync(0xffffffffu, c, 0);
        const uint32_t wc = wo + (c < 7 ? c * 448 : 3072);
#pragma unroll
        for (int kk = 0; kk < 4; kk++) {
          if (kk % AGRP == 0) wg_fence();
          mma_n112_ss_tb(o, desc(oa + (n & 3) * 512 + kk * 2), desc(wc + kk * 128), kk ? 1 : i);
          if (kk % AGRP == AGRP - 1) { wg_commit(); wg_wait<0>(); }
        }
        mbar_arrive_if(bar + 8 * (B_EMPTYWA + (n & 3)), t == 0);
        done |= 1u << c;
        mbar_arrive_if(bar + 8 * (B_EMPTYXA - 1) + 8 * c, t == 0 && ((done << 1) >> c & 1));
        mbar_arrive_if(bar + 8 * B_EMPTYXA + 8 * c, t == 32 && (done >> (c + 1) & 1));
      }
      pin(o);
#pragma unroll
      for (int m = 0; m < 2; m++) {
        uint32_t v[14];
#pragma unroll
        for (int i = 0; i < 14; i++) v[i] = pack_b(o[28 * m + 2 * i], o[28 * m + 2 * i + 1]);
        stage56(sb + SM_WA + m * 7168 + warp * (16 * 112), v, lane);
      }
      fence_async_smem();
      named_sync(1, 128);
      if (t == 0) {
        tma_store(&P.outs, cg * 112, G * 64, sb + SM_WA);
        tma_store(&P.outs, cg * 112 + 56, G * 64, sb + SM_WA + 7168);
        bulk_commit();
        asm volatile("cp.async.bulk.wait_group 0;" ::: "memory");
      }
    }
    if (t == 0) TSTAMP(19);
    }
  }
}

typedef CUresult (*EncodeFn)(CUtensorMap*, CUtensorMapDataType, cuuint32_t, void*, const cuuint64_t*, const cuuint64_t*,
                             const cuuint32_t*, const cuuint32_t*, CUtensorMapInterleave, CUtensorMapSwizzle,
                             CUtensorMapL2promotion, CUtensorMapFloatOOBfill);

void make_map(EncodeFn enc, CUtensorMap* m, const void* ptr, uint64_t rows, uint64_t cols, uint32_t box_rows,
              uint32_t box_cols = 64) {
  cuuint64_t dims[2] = {cols, rows};
  cuuint64_t strides[1] = {cols * 2};
  cuuint32_t box[2] = {box_cols, box_rows};
  cuuint32_t es[2] = {1, 1};
  enc(m, CU_TENSOR_MAP_DATA_TYPE_BFLOAT16, 2, const_cast<void*>(ptr), dims, strides, box, es,
      CU_TENSOR_MAP_INTERLEAVE_NONE, box_cols == 64 ? CU_TENSOR_MAP_SWIZZLE_128B : CU_TENSOR_MAP_SWIZZLE_NONE,
      CU_TENSOR_MAP_L2_PROMOTION_L2_128B,
      CU_TENSOR_MAP_FLOAT_OOB_FILL_NONE);
}

}

#define DEV_FORCE_SLOW 0

extern "C" void kernel_launch(void* const* d_in, const int* in_sizes, int n_in, void* d_out, int out_size) {
  static EncodeFn enc = nullptr;
  static void *kv, *oA, *oB, *kvf, *part, *stats, *flags, *epoch;
  if (!enc) {
    void* fn = nullptr;
    cudaDriverEntryPointQueryResult q;
    cudaGetDriverEntryPoint("cuTensorMapEncodeTiled", &fn, cudaEnableDefault, &q);
    enc = (EncodeFn)fn;
    cudaGetSymbolAddress(&kv, g_kv);
    cudaGetSymbolAddress(&oA, g_oA);
    cudaGetSymbolAddress(&oB, g_oB);
    cudaGetSymbolAddress(&kvf, g_kvf);
    cudaGetSymbolAddress(&part, g_part);
    cudaGetSymbolAddress(&stats, g_stats);
    cudaGetSymbolAddress(&flags, g_flags);
    cudaGetSymbolAddress(&epoch, g_epoch);
    cudaFuncSetAttribute(fused_kernel, cudaFuncAttributeMaxDynamicSharedMemorySize, SMEM_BYTES);
  }
  Params P;
  make_map(enc, &P.xA, d_in[0], S_LEN, DM, 128);
  make_map(enc, &P.wA, d_in[1], DM, 3 * DM, 64);
  make_map(enc, &P.woA, d_in[2], DM, DM, 64);
  make_map(enc, &P.xB, d_in[3], S_LEN, DM, 128);
  make_map(enc, &P.wBh, d_in[4], DM, 3 * DM, 32);
  make_map(enc, &P.woB, d_in[5], DM, DM, 64);
  make_map(enc, &P.kv, kv, 16 * S_LEN, 64, 64);
  make_map(enc, &P.oA, oA, S_LEN, 512, 64);
  make_map(enc, &P.oB, oB, S_LEN, 512, 64);
  make_map(enc, &P.outs, d_out, S_LEN, 2 * DM, 64, 56);
  P.xBp = (const __nv_bfloat16*)d_in[3];
  P.wBp = (const __nv_bfloat16*)d_in[4];
  P.part = (uint4*)part;
  P.kvf = (uint2*)kvf;
  P.stats = (unsigned long long*)stats;
  P.flags = (unsigned*)flags;
  P.epoch = (unsigned*)epoch;
  P.force_slow = DEV_FORCE_SLOW;
  P.zero = 0;
  fused_kernel<<<128, 512, SMEM_BYTES>>>(P);
}
```

```cpp
#include <cuda_runtime.h>
#include <cuda_bf16.h>
#include <cuda_fp16.h>
#include <cuda.h>
#include <stdint.h>

namespace {

constexpr int S_LEN = 2048, DM = 448, DH = 28;
constexpr float QSCALE = 0.18898223650461362f * 1.4426950408889634f;

constexpr uint32_t SM_KV = 0;
constexpr uint32_t SM_XA = 65536;
constexpr uint32_t SM_WA = 180224;
constexpr uint32_t SM_STG = 212992;
constexpr uint32_t SM_BAR = 229376;
constexpr uint32_t SM_STAT = SM_BAR + 576;
constexpr uint32_t SM_ORDER = SM_STAT + 16;
constexpr uint32_t SM_EYE = SM_BAR + 1024;
constexpr uint32_t SMEM_BYTES = SM_BAR + 2048 + 1024;

__device__ __forceinline__ constexpr uint32_t head_slot(int i) { return i < 2 ? 32768 + i * 16384 : SM_WA + (i - 2) * 16384; }

enum {
  B_FULLH = 0, B_FULLKV = 7, B_EMPTYKV = 11, B_OWNRDY = 15, B_STOREDONE = 16, B_STOREDONE1 = 17,
  B_FULLXA = 18, B_FULLWA = 25, B_EMPTYWA = 29, B_XAFREE = 33, B_STGFREE = 34, B_STATS = 35, B_ATTNDONE = 36,
  B_FULLWOB = 37, B_LOOPDONE = 38, B_PUBA = 39, B_EMPTYXA = 40, B_FULLOB = 47, B_HEADDONE = 55, B_FULLQ = 56,
  B_EMPTYH = 63, B_COUNT = 69
};

enum { F_KV = 0, F_OA = 256, F_OB = 384, F_COUNT = 512 };
__device__ __align__(1024) __half g_kv[16 * S_LEN * 64];
__device__ __align__(1024) __nv_bfloat16 g_oA[S_LEN * 512];
__device__ __align__(1024) __nv_bfloat16 g_oB[S_LEN * 512];
__device__ __align__(1024) uint4 g_part[8 * 16 * 56 * 32];
__device__ __align__(1024) uint2 g_kvf[8 * 64 * 32];
__device__ __align__(1024) unsigned long long g_stats[8 * 64 * 2];
__device__ __align__(1024) unsigned g_flags[F_COUNT];
__device__ unsigned g_epoch = 1;
#define TSTAMP(i) do {} while (0)
#define GSTAMP(i) do {} while (0)
#define TDUMP() do {} while (0)
#define ISTAMP(i, v) do {} while (0)

struct __align__(64) Params {
  CUtensorMap xB, wBh, xA, wA, woA, woB, kv, oA, oB, outs;
  const __nv_bfloat16* xBp;
  const __nv_bfloat16* wBp;
  uint4* part;
  uint2* kvf;
  unsigned long long* stats;
  unsigned* flags;
  unsigned* epoch;
  int force_slow;
  uint32_t zero;
};

constexpr uint32_t SPIN_LIMIT = 1u << 24;
#define AWAIT 3
#define AFLY 2
#define OHALF 1
#define AEARLY 1
#define WORD 0
#define WOFF 0
#define BBK 0
#define SMAP 0
#define BMAP 1
#define QK0 1
#define QPRE 0
#define AGRP 2
constexpr bool A_ON = true;

__device__ __forceinline__ void trap_now() { asm volatile("st.global.u32 [%0], %1;" ::"l"(0ull), "r"(0) : "memory"); }
__device__ __forceinline__ void mbar_init(uint32_t a, uint32_t c) {
  asm volatile("mbarrier.init.shared::cta.b64 [%0], %1;" ::"r"(a), "r"(c));
}
__device__ __forceinline__ void mbar_expect(uint32_t a, uint32_t bytes) {
  asm volatile("mbarrier.arrive.expect_tx.shared::cta.b64 _, [%0], %1;" ::"r"(a), "r"(bytes) : "memory");
}
__device__ __forceinline__ void mbar_arrive(uint32_t a) {
  asm volatile("mbarrier.arrive.shared::cta.b64 _, [%0];" ::"r"(a) : "memory");
}
__device__ __forceinline__ void mbar_arrive_if(uint32_t a, bool c) {
  asm volatile("{\n.reg .pred p;\nsetp.ne.b32 p, %1, 0;\n@p mbarrier.arrive.shared::cta.b64 _, [%0];\n}" ::"r"(a),
               "r"((uint32_t)c) : "memory");
}
__device__ __forceinline__ void mbar_arrive_cluster_if(uint32_t a, bool c) {
  asm volatile("{\n.reg .pred p;\nsetp.ne.b32 p, %1, 0;\n@p mbarrier.arrive.shared::cluster.b64 _, [%0];\n}" ::"r"(a),
               "r"((uint32_t)c) : "memory");
}
__device__ __forceinline__ uint32_t mbar_test(uint32_t a, uint32_t parity) {
  uint32_t ok;
  asm volatile("{\n.reg .pred p;\nmbarrier.test_wait.parity.shared::cta.b64 p, [%1], %2;\nselp.u32 %0, 1, 0, p;\n}"
               : "=r"(ok) : "r"(a), "r"(parity) : "memory");
  return ok;
}
__device__ __forceinline__ void mbar_wait(uint32_t a, uint32_t parity, uint32_t have = 0) {
  asm volatile(
      "{\n.reg .pred p;\nsetp.ne.u32 p, %2, 0;\n@p bra.uni DONE;\n"
      "SPIN:\nmbarrier.try_wait.parity.shared::cta.b64 p, [%0], %1;\n@!p bra.uni SPIN;\nDONE:\n}"
      ::"r"(a), "r"(parity), "r"(have) : "memory");
}
__device__ __forceinline__ uint32_t mapa(uint32_t a, uint32_t rank) {
  uint32_t r;
  asm("mapa.shared::cluster.u32 %0, %1, %2;" : "=r"(r) : "r"(a), "r"(rank));
  return r;
}
__device__ __forceinline__ bool elect() {
  uint32_t p;
  asm volatile("{\n.reg .pred P;\nelect.sync _|P, 0xffffffff;\nselp.u32 %0, 1, 0, P;\n}" : "=r"(p));
  return p;
}
__device__ __forceinline__ void tma_load(uint32_t dst, const CUtensorMap* m, int c0, int c1, uint32_t bar) {
  asm volatile("cp.async.bulk.tensor.2d.shared::cluster.global.mbarrier::complete_tx::bytes [%0], [%1, {%3, %4}], [%2];"
               ::"r"(dst), "l"(m), "r"(bar), "r"(c0), "r"(c1) : "memory");
}
__device__ __forceinline__ void tma_load_mc(uint32_t dst, const CUtensorMap* m, int c0, int c1, uint32_t bar) {
  asm volatile(
      "cp.async.bulk.tensor.2d.shared::cluster.global.mbarrier::complete_tx::bytes.multicast::cluster [%0], [%1, {%3, %4}], [%2], %5;"
      ::"r"(dst), "l"(m), "r"(bar), "r"(c0), "r"(c1), "h"((uint16_t)3) : "memory");
}
__device__ __forceinline__ void tma_store(const CUtensorMap* m, int c0, int c1, uint32_t src) {
  asm volatile("cp.async.bulk.tensor.2d.global.shared::cta.bulk_group [%0, {%2, %3}], [%1];" ::"l"(m), "r"(src),
               "r"(c0), "r"(c1) : "memory");
}
__device__ __forceinline__ void tma_prefetch_l2(const CUtensorMap* m, int c0, int c1) {
  asm volatile("cp.async.bulk.prefetch.tensor.2d.L2.global [%0, {%1, %2}];" ::"l"(m), "r"(c0), "r"(c1) : "memory");
}
__device__ __forceinline__ void prefetch_map(const CUtensorMap* m) {
  asm volatile("prefetch.tensormap [%0];" ::"l"(m) : "memory");
}
__device__ __forceinline__ void fence_async_smem() { asm volatile("fence.proxy.async.shared::cta;" ::: "memory"); }
__device__ __forceinline__ void fence_async_all() { asm volatile("fence.proxy.async.global;" ::: "memory"); }
__device__ __forceinline__ void named_sync(int id, int n) { asm volatile("bar.sync %0, %1;" ::"r"(id), "r"(n) : "memory"); }
__device__ __forceinline__ bool named_or(int id, int n, bool v) {
  uint32_t r;
  asm volatile("{\n.reg .pred p, q;\nsetp.ne.b32 p, %3, 0;\nbarrier.red.or.pred q, %1, %2, p;\nselp.u32 %0, 1, 0, q;\n}"
               : "=r"(r) : "r"(id), "r"(n), "r"((uint32_t)v) : "memory");
  return r;
}
__device__ __forceinline__ unsigned ld_flag(const unsigned* p) {
  unsigned v;
  asm volatile("ld.relaxed.gpu.global.u32 %0, [%1];" : "=r"(v) : "l"(p) : "memory");
  return v;
}
__device__ __forceinline__ void bulk_commit() { asm volatile("cp.async.bulk.commit_group;" ::: "memory"); }
__device__ __forceinline__ void bulk_wait() {
  asm volatile("cp.async.bulk.wait_group 0;" ::: "memory");
  asm volatile("fence.proxy.async.global;" ::: "memory");
}
__device__ __forceinline__ void st_release(unsigned* p, unsigned v) {
  asm volatile("st.release.gpu.global.u32 [%0], %1;" ::"l"(p), "r"(v) : "memory");
}
__device__ __forceinline__ void poll_flags(const unsigned* flags, int n, unsigned tag, int lane) {
  uint32_t it = 0;
  while (true) {
    bool ok = lane >= n || ld_flag(flags + lane) == tag;
    if (__all_sync(0xffffffffu, ok)) break;
    if (++it > SPIN_LIMIT) trap_now();
  }
  __syncwarp();
}

__device__ __forceinline__ void poll_tags(const unsigned* w, unsigned tag) {
  uint32_t it = 0;
  while (!__all_sync(0xffffffffu, ld_flag(w) == tag)) {
    if (++it > SPIN_LIMIT) trap_now();
    __nanosleep(300);
  }
}
__device__ __forceinline__ void wg_fence() { asm volatile("wgmma.fence.sync.aligned;" ::: "memory"); }
__device__ __forceinline__ void wg_commit() { asm volatile("wgmma.commit_group.sync.aligned;" ::: "memory"); }
template <int N> __device__ __forceinline__ void wg_wait() { asm volatile("wgmma.wait_group.sync.aligned %0;" ::"n"(N) : "memory"); }
template <int N> __device__ __forceinline__ void pin(float (&a)[N]) {
#pragma unroll
  for (int i = 0; i < N; i++) asm volatile("" : "+f"(a[i])::"memory");
}
template <int N> __device__ __forceinline__ void pin(uint32_t (&a)[N]) {
#pragma unroll
  for (int i = 0; i < N; i++) asm volatile("" : "+r"(a[i])::"memory");
}
__device__ __forceinline__ uint64_t desc(uint32_t lo) { return (uint64_t)0x40000040u << 32 | lo; }
__device__ __forceinline__ uint32_t desc_lo(uint32_t addr, uint32_t lbo) { return ((addr & 0x3FFFF) >> 4) | ((lbo >> 4) << 16); }

__device__ __forceinline__ void stsm4(uint32_t addr, uint32_t r0, uint32_t r1, uint32_t r2, uint32_t r3) {
  asm volatile("stmatrix.sync.aligned.m8n8.x4.shared.b16 [%0], {%1, %2, %3, %4};" ::"r"(addr), "r"(r0), "r"(r1),
               "r"(r2), "r"(r3) : "memory");
}
__device__ __forceinline__ void stsm2(uint32_t addr, uint32_t r0, uint32_t r1) {
  asm volatile("stmatrix.sync.aligned.m8n8.x2.shared.b16 [%0], {%1, %2};" ::"r"(addr), "r"(r0), "r"(r1) : "memory");
}
__device__ __forceinline__ void stage56(uint32_t base, const uint32_t (&v)[14], int lane) {
  const uint32_t a = base + (lane & 15) * 112 + (lane >> 4) * 16;
  stsm4(a, v[0], v[1], v[2], v[3]);
  stsm4(a + 32, v[4], v[5], v[6], v[7]);
  stsm4(a + 64, v[8], v[9], v[10], v[11]);
  stsm2(a + 96, v[12], v[13]);
}
__device__ __forceinline__ void stage64(uint32_t base, const uint32_t (&v)[14], int lane, int off) {
  const uint32_t a = base + (lane & 15) * 128, c = off + (lane >> 4), x = lane & 7;
  stsm4(a + ((c ^ x) << 4), v[0], v[1], v[2], v[3]);
  stsm4(a + (((c + 2) ^ x) << 4), v[4], v[5], v[6], v[7]);
  stsm4(a + (((c + 4) ^ x) << 4), v[8], v[9], v[10], v[11]);
  stsm4(a + ((((c + 6) & 7) ^ x) << 4), v[12], v[13], 0, 0);
}
__device__ __forceinline__ uint32_t pack_h(float lo, float hi) {
  uint32_t r;
  asm("cvt.rn.f16x2.f32 %0, %1, %2;" : "=r"(r) : "f"(hi), "f"(lo));
  return r;
}
__device__ __forceinline__ uint32_t pack_b(float lo, float hi) {
  uint32_t r;
  asm("cvt.rn.bf16x2.f32 %0, %1, %2;" : "=r"(r) : "f"(hi), "f"(lo));
  return r;
}
__device__ __forceinline__ uint32_t ex2_h2(uint32_t x) {
  uint32_t y;
  asm("ex2.approx.f16x2 %0, %1;" : "=r"(y) : "r"(x));
  return y;
}
__device__ __forceinline__ float ex2_f(float x) {
  float y;
  asm("ex2.approx.ftz.f32 %0, %1;" : "=f"(y) : "f"(x));
  return y;
}
__device__ __forceinline__ float rcp_f(float x) {
  float y;
  asm("rcp.approx.f32 %0, %1;" : "=f"(y) : "f"(x));
  return y;
}
__device__ __forceinline__ uint32_t hfma2(uint32_t a, uint32_t b, uint32_t c) {
  uint32_t y;
  asm("fma.rn.f16x2 %0, %1, %2, %3;" : "=r"(y) : "r"(a), "r"(b), "r"(c));
  return y;
}
__device__ __forceinline__ uint32_t habsmax2(uint32_t m, uint32_t a) {
  uint32_t y;
  asm("max.f16x2 %0, %1, %2;" : "=r"(y) : "r"(m), "r"(a & 0x7fff7fffu));
  return y;
}
__device__ __forceinline__ float h_lo(uint32_t v) { return __half2float(__ushort_as_half((unsigned short)(v & 0xffff))); }
__device__ __forceinline__ float h_hi(uint32_t v) { return __half2float(__ushort_as_half((unsigned short)(v >> 16))); }
__device__ __forceinline__ uint32_t phi2(float a, float b) {
  const float ea = ex2_f(fminf(a * 1.4426950408889634f, 0.f)), eb = ex2_f(fminf(b * 1.4426950408889634f, 0.f));
  return pack_b(fmaxf(a, 0.f) + ea + 1e-6f, fmaxf(b, 0.f) + eb + 1e-6f);
}

__device__ __forceinline__ void mma_n128_ss_tb(float (&d)[64], uint64_t a, uint64_t b, int acc) {
  asm volatile("{\n.reg .pred p;\nsetp.ne.b32 p, %66, 0;\n"
    "wgmma.mma_async.sync.aligned.m64n128k16.f32.bf16.bf16 "
    "{%0,%1,%2,%3,%4,%5,%6,%7,%8,%9,%10,%11,%12,%13,%14,%15,%16,%17,%18,%19,%20,%21,%22,%23,%24,%25,%26,%27,%28,%29,%30,%31,%32,%33,%34,%35,%36,%37,%38,%39,%40,%41,%42,%43,%44,%45,%46,%47,%48,%49,%50,%51,%52,%53,%54,%55,%56,%57,%58,%59,%60,%61,%62,%63}, "
    "%64, %65, p, 1, 1, 0, 1;\n}\n"
    : "+f"(d[0]), "+f"(d[1]), "+f"(d[2]), "+f"(d[3]), "+f"(d[4]), "+f"(d[5]), "+f"(d[6]), "+f"(d[7]),
      "+f"(d[8]), "+f"(d[9]), "+f"(d[10]), "+f"(d[11]), "+f"(d[12]), "+f"(d[13]), "+f"(d[14]), "+f"(d[15]),
      "+f"(d[16]), "+f"(d[17]), "+f"(d[18]), "+f"(d[19]), "+f"(d[20]), "+f"(d[21]), "+f"(d[22]), "+f"(d[23]),
      "+f"(d[24]), "+f"(d[25]), "+f"(d[26]), "+f"(d[27]), "+f"(d[28]), "+f"(d[29]), "+f"(d[30]), "+f"(d[31]),
      "+f"(d[32]), "+f"(d[33]), "+f"(d[34]), "+f"(d[35]), "+f"(d[36]), "+f"(d[37]), "+f"(d[38]), "+f"(d[39]),
      "+f"(d[40]), "+f"(d[41]), "+f"(d[42]), "+f"(d[43]), "+f"(d[44]), "+f"(d[45]), "+f"(d[46]), "+f"(d[47]),
      "+f"(d[48]), "+f"(d[49]), "+f"(d[50]), "+f"(d[51]), "+f"(d[52]), "+f"(d[53]), "+f"(d[54]), "+f"(d[55]),
      "+f"(d[56]), "+f"(d[57]), "+f"(d[58]), "+f"(d[59]), "+f"(d[60]), "+f"(d[61]), "+f"(d[62]), "+f"(d[63])
    : "l"(a), "l"(b), "r"(acc));
}
__device__ __forceinline__ void mma_qk(uint32_t (&d)[16], uint32_t a0, uint32_t a1, uint32_t a2, uint32_t a3, uint64_t b, int acc) {
  asm volatile("{\n.reg .pred p;\nsetp.ne.b32 p, %21, 0;\n"
    "wgmma.mma_async.sync.aligned.m64n64k16.f16.f16.f16 "
    "{%0,%1,%2,%3,%4,%5,%6,%7,%8,%9,%10,%11,%12,%13,%14,%15}, "
    "{%16,%17,%18,%19}, %20, p, 1, 1, 0;\n}\n"
    : "+r"(d[0]), "+r"(d[1]), "+r"(d[2]), "+r"(d[3]), "+r"(d[4]), "+r"(d[5]), "+r"(d[6]), "+r"(d[7]),
      "+r"(d[8]), "+r"(d[9]), "+r"(d[10]), "+r"(d[11]), "+r"(d[12]), "+r"(d[13]), "+r"(d[14]), "+r"(d[15])
    : "r"(a0), "r"(a1), "r"(a2), "r"(a3), "l"(b), "r"(acc));
}
__device__ __forceinline__ void mma_qk0(uint32_t (&d)[16], uint32_t a0, uint32_t a1, uint32_t a2, uint32_t a3, uint64_t b) {
  asm volatile("{\n.reg .pred p;\nsetp.ne.b32 p, %21, 0;\n"
    "wgmma.mma_async.sync.aligned.m64n64k16.f16.f16.f16 "
    "{%0,%1,%2,%3,%4,%5,%6,%7,%8,%9,%10,%11,%12,%13,%14,%15}, "
    "{%16,%17,%18,%19}, %20, p, 1, 1, 0;\n}\n"
    : "=r"(d[0]), "=r"(d[1]), "=r"(d[2]), "=r"(d[3]), "=r"(d[4]), "=r"(d[5]), "=r"(d[6]), "=r"(d[7]),
      "=r"(d[8]), "=r"(d[9]), "=r"(d[10]), "=r"(d[11]), "=r"(d[12]), "=r"(d[13]), "=r"(d[14]), "=r"(d[15])
    : "r"(a0), "r"(a1), "r"(a2), "r"(a3), "l"(b), "n"(0));
}
__device__ __forceinline__ void mma_pv_h0(uint32_t (&d)[8], uint32_t a0, uint32_t a1, uint32_t a2, uint32_t a3, uint64_t b) {
  asm volatile("{\n.reg .pred p;\nsetp.ne.b32 p, %13, 0;\n"
    "wgmma.mma_async.sync.aligned.m64n32k16.f16.f16.f16 "
    "{%0,%1,%2,%3,%4,%5,%6,%7}, "
    "{%8,%9,%10,%11}, %12, p, 1, 1, 1;\n}\n"
    : "=r"(d[0]), "=r"(d[1]), "=r"(d[2]), "=r"(d[3]), "=r"(d[4]), "=r"(d[5]), "=r"(d[6]), "=r"(d[7])
    : "r"(a0), "r"(a1), "r"(a2), "r"(a3), "l"(b), "n"(0));
}
__device__ __forceinline__ void mma_pv(float (&d)[16], uint32_t a0, uint32_t a1, uint32_t a2, uint32_t a3, uint64_t b, int acc) {
  asm volatile("{\n.reg .pred p;\nsetp.ne.b32 p, %21, 0;\n"
    "wgmma.mma_async.sync.aligned.m64n32k16.f32.f16.f16 "
    "{%0,%1,%2,%3,%4,%5,%6,%7,%8,%9,%10,%11,%12,%13,%14,%15}, "
    "{%16,%17,%18,%19}, %20, p, 1, 1, 1;\n}\n"
    : "+f"(d[0]), "+f"(d[1]), "+f"(d[2]), "+f"(d[3]), "+f"(d[4]), "+f"(d[5]), "+f"(d[6]), "+f"(d[7]),
      "+f"(d[8]), "+f"(d[9]), "+f"(d[10]), "+f"(d[11]), "+f"(d[12]), "+f"(d[13]), "+f"(d[14]), "+f"(d[15])
    : "r"(a0), "r"(a1), "r"(a2), "r"(a3), "l"(b), "r"(acc));
}
__device__ __forceinline__ void mma_pv_h(uint32_t (&d)[8], uint32_t a0, uint32_t a1, uint32_t a2, uint32_t a3, uint64_t b, int acc) {
  asm volatile("{\n.reg .pred p;\nsetp.ne.b32 p, %13, 0;\n"
    "wgmma.mma_async.sync.aligned.m64n32k16.f16.f16.f16 "
    "{%0,%1,%2,%3,%4,%5,%6,%7}, "
    "{%8,%9,%10,%11}, %12, p, 1, 1, 1;\n}\n"
    : "+r"(d[0]), "+r"(d[1]), "+r"(d[2]), "+r"(d[3]), "+r"(d[4]), "+r"(d[5]), "+r"(d[6]), "+r"(d[7])
    : "r"(a0), "r"(a1), "r"(a2), "r"(a3), "l"(b), "r"(acc));
}
__device__ __forceinline__ void mma_fl(float (&d)[8], uint32_t a0, uint32_t a1, uint32_t a2, uint32_t a3, uint64_t b, int acc) {
  asm volatile("{\n.reg .pred p;\nsetp.ne.b32 p, %13, 0;\n"
    "wgmma.mma_async.sync.aligned.m64n16k16.f32.f16.f16 "
    "{%0,%1,%2,%3,%4,%5,%6,%7}, "
    "{%8,%9,%10,%11}, %12, p, 1, 1, 0;\n}\n"
    : "+f"(d[0]), "+f"(d[1]), "+f"(d[2]), "+f"(d[3]), "+f"(d[4]), "+f"(d[5]), "+f"(d[6]), "+f"(d[7])
    : "r"(a0), "r"(a1), "r"(a2), "r"(a3), "l"(b), "r"(acc));
}
__device__ __forceinline__ void mma_n128_ss_ta(float (&d)[64], uint64_t a, uint64_t b, int acc) {
  asm volatile("{\n.reg .pred p;\nsetp.ne.b32 p, %66, 0;\n"
    "wgmma.mma_async.sync.aligned.m64n128k16.f32.bf16.bf16 "
    "{%0,%1,%2,%3,%4,%5,%6,%7,%8,%9,%10,%11,%12,%13,%14,%15,%16,%17,%18,%19,%20,%21,%22,%23,%24,%25,%26,%27,%28,%29,%30,%31,%32,%33,%34,%35,%36,%37,%38,%39,%40,%41,%42,%43,%44,%45,%46,%47,%48,%49,%50,%51,%52,%53,%54,%55,%56,%57,%58,%59,%60,%61,%62,%63}, "
    "%64, %65, p, 1, 1, 1, 0;\n}\n"
    : "+f"(d[0]), "+f"(d[1]), "+f"(d[2]), "+f"(d[3]), "+f"(d[4]), "+f"(d[5]), "+f"(d[6]), "+f"(d[7]),
      "+f"(d[8]), "+f"(d[9]), "+f"(d[10]), "+f"(d[11]), "+f"(d[12]), "+f"(d[13]), "+f"(d[14]), "+f"(d[15]),
      "+f"(d[16]), "+f"(d[17]), "+f"(d[18]), "+f"(d[19]), "+f"(d[20]), "+f"(d[21]), "+f"(d[22]), "+f"(d[23]),
      "+f"(d[24]), "+f"(d[25]), "+f"(d[26]), "+f"(d[27]), "+f"(d[28]), "+f"(d[29]), "+f"(d[30]), "+f"(d[31]),
      "+f"(d[32]), "+f"(d[33]), "+f"(d[34]), "+f"(d[35]), "+f"(d[36]), "+f"(d[37]), "+f"(d[38]), "+f"(d[39]),
      "+f"(d[40]), "+f"(d[41]), "+f"(d[42]), "+f"(d[43]), "+f"(d[44]), "+f"(d[45]), "+f"(d[46]), "+f"(d[47]),
      "+f"(d[48]), "+f"(d[49]), "+f"(d[50]), "+f"(d[51]), "+f"(d[52]), "+f"(d[53]), "+f"(d[54]), "+f"(d[55]),
      "+f"(d[56]), "+f"(d[57]), "+f"(d[58]), "+f"(d[59]), "+f"(d[60]), "+f"(d[61]), "+f"(d[62]), "+f"(d[63])
    : "l"(a), "l"(b), "r"(acc));
}
__device__ __forceinline__ void mma_n64_rs(float (&d)[32], uint32_t a0, uint32_t a1, uint32_t a2, uint32_t a3, uint64_t b, int acc) {
  asm volatile("{\n.reg .pred p;\nsetp.ne.b32 p, %37, 0;\n"
    "wgmma.mma_async.sync.aligned.m64n64k16.f32.bf16.bf16 "
    "{%0,%1,%2,%3,%4,%5,%6,%7,%8,%9,%10,%11,%12,%13,%14,%15,%16,%17,%18,%19,%20,%21,%22,%23,%24,%25,%26,%27,%28,%29,%30,%31}, "
    "{%32,%33,%34,%35}, %36, p, 1, 1, 0;\n}\n"
    : "+f"(d[0]), "+f"(d[1]), "+f"(d[2]), "+f"(d[3]), "+f"(d[4]), "+f"(d[5]), "+f"(d[6]), "+f"(d[7]),
      "+f"(d[8]), "+f"(d[9]), "+f"(d[10]), "+f"(d[11]), "+f"(d[12]), "+f"(d[13]), "+f"(d[14]), "+f"(d[15]),
      "+f"(d[16]), "+f"(d[17]), "+f"(d[18]), "+f"(d[19]), "+f"(d[20]), "+f"(d[21]), "+f"(d[22]), "+f"(d[23]),
      "+f"(d[24]), "+f"(d[25]), "+f"(d[26]), "+f"(d[27]), "+f"(d[28]), "+f"(d[29]), "+f"(d[30]), "+f"(d[31])
    : "r"(a0), "r"(a1), "r"(a2), "r"(a3), "l"(b), "r"(acc));
}
__device__ __forceinline__ void mma_n64_rs_tb(float (&d)[32], uint32_t a0, uint32_t a1, uint32_t a2, uint32_t a3, uint64_t b, int acc) {
  asm volatile("{\n.reg .pred p;\nsetp.ne.b32 p, %37, 0;\n"
    "wgmma.mma_async.sync.aligned.m64n64k16.f32.bf16.bf16 "
    "{%0,%1,%2,%3,%4,%5,%6,%7,%8,%9,%10,%11,%12,%13,%14,%15,%16,%17,%18,%19,%20,%21,%22,%23,%24,%25,%26,%27,%28,%29,%30,%31}, "
    "{%32,%33,%34,%35}, %36, p, 1, 1, 1;\n}\n"
    : "+f"(d[0]), "+f"(d[1]), "+f"(d[2]), "+f"(d[3]), "+f"(d[4]), "+f"(d[5]), "+f"(d[6]), "+f"(d[7]),
      "+f"(d[8]), "+f"(d[9]), "+f"(d[10]), "+f"(d[11]), "+f"(d[12]), "+f"(d[13]), "+f"(d[14]), "+f"(d[15]),
      "+f"(d[16]), "+f"(d[17]), "+f"(d[18]), "+f"(d[19]), "+f"(d[20]), "+f"(d[21]), "+f"(d[22]), "+f"(d[23]),
      "+f"(d[24]), "+f"(d[25]), "+f"(d[26]), "+f"(d[27]), "+f"(d[28]), "+f"(d[29]), "+f"(d[30]), "+f"(d[31])
    : "r"(a0), "r"(a1), "r"(a2), "r"(a3), "l"(b), "r"(acc));
}
__device__ __forceinline__ void mma_n64_ss_tb(float (&d)[32], uint64_t a, uint64_t b, int acc) {
  asm volatile("{\n.reg .pred p;\nsetp.ne.b32 p, %34, 0;\n"
    "wgmma.mma_async.sync.aligned.m64n64k16.f32.bf16.bf16 "
    "{%0,%1,%2,%3,%4,%5,%6,%7,%8,%9,%10,%11,%12,%13,%14,%15,%16,%17,%18,%19,%20,%21,%22,%23,%24,%25,%26,%27,%28,%29,%30,%31}, "
    "%32, %33, p, 1, 1, 0, 1;\n}\n"
    : "+f"(d[0]), "+f"(d[1]), "+f"(d[2]), "+f"(d[3]), "+f"(d[4]), "+f"(d[5]), "+f"(d[6]), "+f"(d[7]),
      "+f"(d[8]), "+f"(d[9]), "+f"(d[10]), "+f"(d[11]), "+f"(d[12]), "+f"(d[13]), "+f"(d[14]), "+f"(d[15]),
      "+f"(d[16]), "+f"(d[17]), "+f"(d[18]), "+f"(d[19]), "+f"(d[20]), "+f"(d[21]), "+f"(d[22]), "+f"(d[23]),
      "+f"(d[24]), "+f"(d[25]), "+f"(d[26]), "+f"(d[27]), "+f"(d[28]), "+f"(d[29]), "+f"(d[30]), "+f"(d[31])
    : "l"(a), "l"(b), "r"(acc));
}
__device__ __forceinline__ void mma_n112_ss_tb(float (&d)[56], uint64_t a, uint64_t b, int acc) {
  asm volatile("{\n.reg .pred p;\nsetp.ne.b32 p, %58, 0;\n"
    "wgmma.mma_async.sync.aligned.m64n112k16.f32.bf16.bf16 "
    "{%0,%1,%2,%3,%4,%5,%6,%7,%8,%9,%10,%11,%12,%13,%14,%15,%16,%17,%18,%19,%20,%21,%22,%23,%24,%25,%26,%27,%28,%29,%30,%31,%32,%33,%34,%35,%36,%37,%38,%39,%40,%41,%42,%43,%44,%45,%46,%47,%48,%49,%50,%51,%52,%53,%54,%55}, "
    "%56, %57, p, 1, 1, 0, 1;\n}\n"
    : "+f"(d[0]), "+f"(d[1]), "+f"(d[2]), "+f"(d[3]), "+f"(d[4]), "+f"(d[5]), "+f"(d[6]), "+f"(d[7]),
      "+f"(d[8]), "+f"(d[9]), "+f"(d[10]), "+f"(d[11]), "+f"(d[12]), "+f"(d[13]), "+f"(d[14]), "+f"(d[15]),
      "+f"(d[16]), "+f"(d[17]), "+f"(d[18]), "+f"(d[19]), "+f"(d[20]), "+f"(d[21]), "+f"(d[22]), "+f"(d[23]),
      "+f"(d[24]), "+f"(d[25]), "+f"(d[26]), "+f"(d[27]), "+f"(d[28]), "+f"(d[29]), "+f"(d[30]), "+f"(d[31]),
      "+f"(d[32]), "+f"(d[33]), "+f"(d[34]), "+f"(d[35]), "+f"(d[36]), "+f"(d[37]), "+f"(d[38]), "+f"(d[39]),
      "+f"(d[40]), "+f"(d[41]), "+f"(d[42]), "+f"(d[43]), "+f"(d[44]), "+f"(d[45]), "+f"(d[46]), "+f"(d[47]),
      "+f"(d[48]), "+f"(d[49]), "+f"(d[50]), "+f"(d[51]), "+f"(d[52]), "+f"(d[53]), "+f"(d[54]), "+f"(d[55])
    : "l"(a), "l"(b), "r"(acc));
}
__device__ __forceinline__ void mma_n56_ss_tb(float (&d)[28], uint64_t a, uint64_t b, int acc) {
  asm volatile("{\n.reg .pred p;\nsetp.ne.b32 p, %30, 0;\n"
    "wgmma.mma_async.sync.aligned.m64n56k16.f32.bf16.bf16 "
    "{%0,%1,%2,%3,%4,%5,%6,%7,%8,%9,%10,%11,%12,%13,%14,%15,%16,%17,%18,%19,%20,%21,%22,%23,%24,%25,%26,%27}, "
    "%28, %29, p, 1, 1, 0, 1;\n}\n"
    : "+f"(d[0]), "+f"(d[1]), "+f"(d[2]), "+f"(d[3]), "+f"(d[4]), "+f"(d[5]), "+f"(d[6]), "+f"(d[7]),
      "+f"(d[8]), "+f"(d[9]), "+f"(d[10]), "+f"(d[11]), "+f"(d[12]), "+f"(d[13]), "+f"(d[14]), "+f"(d[15]),
      "+f"(d[16]), "+f"(d[17]), "+f"(d[18]), "+f"(d[19]), "+f"(d[20]), "+f"(d[21]), "+f"(d[22]), "+f"(d[23]),
      "+f"(d[24]), "+f"(d[25]), "+f"(d[26]), "+f"(d[27])
    : "l"(a), "l"(b), "r"(acc));
}

#define NPOLY 5
#define PGROUP 1
__device__ __forceinline__ uint32_t exp2_fma_h2(uint32_t x, uint32_t magic, uint32_t& chain) {
  uint32_t c, t, n, f;
  asm("min.xorsign.abs.f16x2 %0, %1, %2;" : "=r"(c) : "r"(x), "r"(0x4b004b00u));
  asm("add.rn.f16x2 %0, %1, %2;" : "=r"(t) : "r"(c), "r"(magic));
  asm("sub.rn.f16x2 %0, %1, %2;" : "=r"(n) : "r"(t), "r"(0x66006600u));
  asm("sub.rn.f16x2 %0, %1, %2;" : "=r"(f) : "r"(c), "r"(n));
  uint32_t q = hfma2(0x2af92af9u, f, 0x33be33beu);
  q = hfma2(q, f, 0x398c398cu);
  q = hfma2(q, f, 0x3c003c00u);
  chain = q;
  return q + (t << 10) - 0x01980000u;
}
__device__ __forceinline__ void exp_tile(const uint32_t (&s)[16], uint32_t (&p)[16], uint32_t zero, uint32_t& chain) {
  uint32_t magic = 0x66006600u;
#pragma unroll
  for (int i = 0; i < 16; i++) {
    const int k = i * NPOLY / 16;
    if ((i + 1) * NPOLY / 16 != k) {
      if (k % PGROUP == 0) magic = hfma2(chain, zero, 0x66006600u);
      p[i] = exp2_fma_h2(s[i], magic, chain);
    } else {
      p[i] = ex2_h2(s[i]);
    }
  }
}

__device__ __forceinline__ void slow_project(const __nv_bfloat16* __restrict__ xrow, const __nv_bfloat16* __restrict__ wcol,
                                             float (&o)[DH]) {
#pragma unroll
  for (int d = 0; d < DH; d++) o[d] = 0.f;
#pragma unroll 1
  for (int k = 0; k < DM; k += 2) {
    __nv_bfloat162 xv = *reinterpret_cast<const __nv_bfloat162*>(xrow + k);
#pragma unroll
    for (int u = 0; u < 2; u++) {
      float x = u ? __high2float(xv) : __low2float(xv);
      const uint2* wp = reinterpret_cast<const uint2*>(wcol + (size_t)(k + u) * (3 * DM));
#pragma unroll
      for (int d = 0; d < DH / 4; d++) {
        uint2 w = __ldg(wp + d);
        o[4 * d + 0] = fmaf(x, __uint_as_float(w.x << 16), o[4 * d + 0]);
        o[4 * d + 1] = fmaf(x, __uint_as_float(w.x & 0xffff0000u), o[4 * d + 1]);
        o[4 * d + 2] = fmaf(x, __uint_as_float(w.y << 16), o[4 * d + 2]);
        o[4 * d + 3] = fmaf(x, __uint_as_float(w.y & 0xffff0000u), o[4 * d + 3]);
      }
    }
  }
#pragma unroll
  for (int d = 0; d < DH; d++) o[d] = __bfloat162float(__float2bfloat16(o[d]));
}

__device__ __forceinline__ void slow_attention(const __nv_bfloat16* __restrict__ x, const __nv_bfloat16* __restrict__ w,
                                            float* scratch, uint32_t* stage, int row0, int p, int t, int bar_id) {
  const int head = 2 * p + (t >> 6), row = row0 + (t & 63);
  float q[DH], acc[DH], tmp[DH];
  slow_project(x + (size_t)row * DM, w + head * DH, q);
  float m = -INFINITY, l = 0.f;
#pragma unroll
  for (int d = 0; d < DH; d++) acc[d] = 0.f;
  float* mine = scratch + t * (2 * DH + 1);
  const float* keys = scratch + (t >> 6) * 64 * (2 * DH + 1);
#pragma unroll 1
  for (int kb = 0; kb < S_LEN; kb += 64) {
#pragma unroll 1
    for (int part = 0; part < 2; part++) {
      slow_project(x + (size_t)(kb + (t & 63)) * DM, w + (part + 1) * DM + head * DH, tmp);
#pragma unroll
      for (int d = 0; d < DH; d++) mine[part * DH + d] = tmp[d];
    }
    named_sync(bar_id, 128);
#pragma unroll 1
    for (int j = 0; j < 64; j++) {
      const float* kr = keys + j * (2 * DH + 1);
      float s = 0.f;
#pragma unroll
      for (int d = 0; d < DH; d++) s = fmaf(q[d], kr[d], s);
      s *= 0.18898223650461362f;
      float mn = fmaxf(m, s);
      float a = __expf(m - mn), pj = __expf(s - mn);
      l = l * a + pj;
#pragma unroll
      for (int d = 0; d < DH; d++) acc[d] = fmaf(pj, kr[DH + d], acc[d] * a);
      m = mn;
    }
    named_sync(bar_id, 128);
  }
  float r = rcp_f(l);
#pragma unroll
  for (int d = 0; d < DH; d += 2) {
    const int w = (p == 7) * 4 + (t >> 6) * 14 + (d >> 1);
    stage[(t & 63) * 32 + (((w >> 2) ^ (t & 7)) << 2) + (w & 3)] = pack_b(acc[d] * r, acc[d + 1] * r);
  }
}

__global__ void __cluster_dims__(2, 1, 1) __launch_bounds__(512, 1) fused_kernel(const __grid_constant__ Params P) {
  extern __shared__ uint8_t smem_raw[];
  const uint32_t sb = __shfl_sync(0xffffffffu, ((uint32_t)__cvta_generic_to_shared(smem_raw) + 1023) & ~1023u, 0);
  const uint32_t bar = sb + SM_BAR;
  const int wg = __shfl_sync(0xffffffffu, threadIdx.x >> 7, 0);
  const int warp = __shfl_sync(0xffffffffu, (threadIdx.x >> 5) & 3, 0);
  const int lane = threadIdx.x & 31;
  const int rank = blockIdx.x & 1;
  const int cb = blockIdx.x >> 1;
  const int cl = cb < 4 ? (4 + cb) * 8 : (cb < 36 ? cb - 4 : (4 + (cb - 36) / 7) * 8 + 1 + (cb - 36) % 7);
  const int ci = cl & 7;
  const int p = cl >> 3;
  const int r = 2 * ci + rank;
  const int G = 4 * ci + (p >> 1);
  const int cg = 2 * (p & 1) + rank;
  const int wcol = 56 * p - 8 * (p & 1);

  if (threadIdx.x == 0) { TSTAMP(0); GSTAMP(30); }
  unsigned tag;
  if (wg == 3) {
    asm volatile("setmaxnreg.dec.sync.aligned.u32 32;");
    auto head_x = [&](int c) {
      mbar_expect(bar + 8 * (B_FULLH + c), 32768);
      tma_load(sb + SM_XA + c * 16384, &P.xB, c * 64, r * 128, bar + 8 * (B_FULLH + c));
    };
    if (warp == 0) {
      if (elect()) {
        prefetch_map(&P.xB);
        prefetch_map(&P.wBh);
        mbar_init(bar + 8 * B_FULLH, 1);
        asm volatile("fence.mbarrier_init.release.cluster;" ::: "memory");
        head_x(0);
#pragma unroll
        for (int b = 0; b < 4; b++)
          tma_load(sb + head_slot(0) + b * 4096, &P.wBh, (1 + (b >> 1)) * DM + wcol, (b & 1) * 32, bar + 8 * B_FULLH);
        TSTAMP(11);
      }
      __syncwarp();
      asm volatile("bar.arrive 0, 512;" ::: "memory");
    } else {
      if (elect()) {
#pragma unroll
        for (int w = 1; w < 4; w++) {
          if (warp == w) {
#pragma unroll
            for (int i = w; i < B_COUNT; i += 3) {
              uint32_t c = 1;
              if (i >= B_EMPTYH || (i >= B_EMPTYKV && i < B_EMPTYKV + 4) || i == B_PUBA) c = 4;
              if (i == B_OWNRDY) c = 8;
              if (i == B_STOREDONE) c = 5;
              if (i == B_ATTNDONE || i == B_LOOPDONE || i == B_HEADDONE) c = 2;
              mbar_init(bar + 8 * i, c);
            }
          }
        }
        asm volatile("fence.mbarrier_init.release.cluster;" ::: "memory");
      }
      __syncwarp();
      asm volatile("bar.sync 0, 512;" ::: "memory");
    }
    asm volatile("barrier.cluster.arrive.relaxed.aligned;" ::: "memory");
    asm volatile("ld.volatile.global.u32 %0, [%1];" : "=r"(tag) : "l"(P.epoch));
    if (warp == 0) {
      asm volatile("barrier.cluster.wait.acquire.aligned;" ::: "memory");
      if (elect()) {
#pragma unroll 1
        for (int c = 1; c < 7; c++) {
          head_x(c);
          if (c >= 5) mbar_wait(bar + 8 * (B_EMPTYH + c - 5), 0);
          const uint32_t st = sb + head_slot(c < 5 ? c : c - 5) + rank * 4096;
          tma_load_mc(st, &P.wBh, DM + wcol, c * 64 + rank * 32, bar + 8 * (B_FULLH + c));
          tma_load_mc(st + 8192, &P.wBh, 2 * DM + wcol, c * 64 + rank * 32, bar + 8 * (B_FULLH + c));
          if (c == 4) { TSTAMP(12); prefetch_map(&P.kv); prefetch_map(&P.oB); prefetch_map(&P.outs); }
        }
#pragma unroll 1
        for (int c = 0; c < 7; c++) {
          if (!(c & 1)) mbar_wait(bar + 8 * (B_EMPTYH + 2 + (c >> 1)), 0);
          mbar_expect(bar + 8 * (B_FULLQ + c), 8192);
          tma_load_mc(sb + (c < 6 ? head_slot(2) + c * 8192 : head_slot(0)) + rank * 4096, &P.wBh, wcol, c * 64 + rank * 32,
                      bar + 8 * (B_FULLQ + c));
        }
      }
      __syncwarp();
      uint32_t ready = 0, todo = ~(15u << (4 * ci));
#pragma unroll 1
      for (int j = 2; j < 32; j++) {
        const int s = j & 3;
        uint32_t it = 0;
        const uint32_t want = j < 30 ? todo : 1u << (2 * (r ^ 1) + (j & 1));
        while (!(ready & want)) {
          ready = __ballot_sync(0xffffffffu, ld_flag(&P.flags[F_KV + p * 32 + lane]) == tag);
          if (++it > SPIN_LIMIT) trap_now();
        }
        const uint32_t m = ready & want, hi = m >> (2 * r) << (2 * r);
        const int blk = __ffs(hi ? hi : m) - 1;
        todo &= ~(1u << blk);
        __syncwarp();
        if (elect()) {
          if (it) fence_async_all();
          const uint32_t fb = bar + 8 * (B_FULLKV + s);
          mbar_wait(bar + 8 * (B_EMPTYKV + s), ((j - 2) >> 2) & 1);
          mbar_expect(fb, 16384);
          if (j < 30) {
            tma_load_mc(sb + SM_KV + s * 16384 + rank * 8192, &P.kv, 0, (2 * p + rank) * S_LEN + blk * 64, fb);
          } else {
            tma_load(sb + SM_KV + s * 16384, &P.kv, 0, (2 * p) * S_LEN + blk * 64, fb);
            tma_load(sb + SM_KV + s * 16384 + 8192, &P.kv, 0, (2 * p + 1) * S_LEN + blk * 64, fb);
          }
          if (j == 2) TSTAMP(9);
        }
        __syncwarp();
      }
      if (elect()) mbar_wait(bar + 8 * B_ATTNDONE, 0);
      __syncwarp();
      uint32_t left = 0xff, it = 0;
      int n = 0;
#pragma unroll 1
      while (left) {
        uint32_t m = left & __ballot_sync(0xffffffffu, lane < 8 && ld_flag(&P.flags[F_OB + (G >> 1) * 8 + lane]) == tag);
        if (++it > SPIN_LIMIT) trap_now();
        left &= ~m;
        if (m && elect()) {
          fence_async_all();
#pragma unroll 1
          for (int k = n; m; k++, m &= m - 1) {
            const int c = __ffs(m) - 1;
            asm volatile("st.shared.u32 [%0], %1;" ::"r"(sb + SM_ORDER + 4 * k), "r"(c < 7 ? c * 448 : 3072) : "memory");
            mbar_expect(bar + 8 * (B_FULLOB + k), 8192);
            tma_load(sb + SM_KV + k * 8192, &P.oB, c * 64, G * 64, bar + 8 * (B_FULLOB + k));
            if (k == 7) TSTAMP(10);
          }
        }
        __syncwarp();
        n = 8 - __popc(left);
      }
    } else if (warp == 1) {
      if (A_ON && elect()) {
        prefetch_map(&P.xA);
        prefetch_map(&P.wA);
        mbar_wait(bar + 8 * (B_EMPTYH + 1), 0);
        if (tag == 0) trap_now();
        if (p < 7) tma_prefetch_l2(&P.xA, p * 64, r * 128);
#pragma unroll 1
        for (int b = 0; b < 3; b++) tma_prefetch_l2(&P.wA, (2 - b) * DM + wcol, (r % 7) * 64);
        prefetch_map(&P.woA);
        prefetch_map(&P.woB);
        prefetch_map(&P.oA);
        mbar_wait(bar + 8 * B_HEADDONE, 0);
        int c = 6, col = 2 * DM + wcol;
#pragma unroll 1
        for (int n = 0; n < 21; n++) {
          const int s = n & 3;
          if (n < 7) {
            if (n == AEARLY) mbar_wait(bar + 8 * (B_FULLKV + AWAIT), 0);
            if (n > AFLY) mbar_wait(bar + 8 * (B_FULLXA + n - 1 - AFLY), 0);
            mbar_expect(bar + 8 * (B_FULLXA + c), 16384);
            tma_load(sb + SM_XA + c * 16384, &P.xA, c * 64, r * 128, bar + 8 * (B_FULLXA + c));
          }
          if (n >= 4) mbar_wait(bar + 8 * (B_EMPTYWA + s), ((n >> 2) - 1) & 1);
          mbar_expect(bar + 8 * (B_FULLWA + s), 8192);
          tma_load(sb + SM_WA + s * 8192, &P.wA, col, c * 64, bar + 8 * (B_FULLWA + s));
          if (++c == 7) c = 0;
          if (c == 6) col -= DM;
        }
        mbar_wait(bar + 8 * B_XAFREE, 0);
#pragma unroll 1
        for (int n = 0; n < 7; n++) {
          const uint32_t fb = bar + 8 * (B_FULLXA + n);
          if (n >= 2) mbar_wait(fb - 16, 1);
          mbar_expect(fb, 16384);
          tma_load(sb + SM_XA + n * 8192, &P.woA, cg * 112, n * 64, fb);
          tma_load(sb + SM_XA + 57344 + n * 8192, &P.woA, cg * 112 + 64, n * 64, fb);
        }
      }
      __syncwarp();
      uint32_t left = A_ON ? 0xff : 0, it = 0;
      int n = 21;
#pragma unroll 1
      while (left) {
        uint32_t m = left & __ballot_sync(0xffffffffu, lane < 8 && ld_flag(&P.flags[F_OA + (G >> 1) * 8 + lane]) == tag);
        if (++it > SPIN_LIMIT) trap_now();
        left &= ~m;
        if (!m) { __nanosleep(200); continue; }
        if (elect()) {
          fence_async_all();
#pragma unroll 1
          for (int k = n; m; k++, m &= m - 1) {
            const int c = __ffs(m) - 1, s = k & 3;
            mbar_wait(bar + 8 * (B_EMPTYWA + s), ((k >> 2) - 1) & 1);
            asm volatile("st.shared.u32 [%0], %1;" ::"r"(sb + SM_ORDER + 32 + 4 * (k - 21)), "r"(c) : "memory");
            mbar_expect(bar + 8 * (B_FULLWA + s), 8192);
            tma_load(sb + SM_WA + s * 8192, &P.oA, c * 64, G * 64, bar + 8 * (B_FULLWA + s));
          }
        }
        __syncwarp();
        n = 29 - __popc(left);
      }
    } else if (warp == 2) {
      if (elect()) {
        mbar_wait(bar + 8 * B_OWNRDY, 0);
        TSTAMP(15);
#pragma unroll 1
        for (int h = 0; h < 2; h++) {
          tma_store(&P.kv, 0, (2 * p) * S_LEN + r * 128 + h * 64, sb + SM_KV + h * 16384);
          tma_store(&P.kv, 0, (2 * p + 1) * S_LEN + r * 128 + h * 64, sb + SM_KV + h * 16384 + 8192);
          bulk_commit();
          bulk_wait();
          mbar_arrive(bar + 8 * (B_STOREDONE + h));
          st_release(&P.flags[F_KV + p * 32 + 2 * r + h], tag);
          if (h == 0) TSTAMP(14); else TSTAMP(8);
        }
        if (A_ON) {
          mbar_wait(bar + 8 * B_PUBA, 0);
          tma_store(&P.oA, 64 * p, r * 128, sb + SM_STG);
          tma_store(&P.oA, 64 * p, r * 128 + 64, sb + SM_STG + 8192);
          bulk_commit();
          bulk_wait();
        }
        mbar_arrive(bar + 8 * B_STGFREE);
        if (A_ON) st_release(&P.flags[F_OA + r * 8 + p], tag);
        TSTAMP(20);
        mbar_wait(bar + 8 * B_ATTNDONE, 0);
        tma_store(&P.oB, 64 * p, r * 128, sb + SM_STG);
        tma_store(&P.oB, 64 * p, r * 128 + 64, sb + SM_STG + 8192);
        bulk_commit();
        bulk_wait();
        TSTAMP(13);
        mbar_arrive(bar + 8 * B_STGFREE);
        st_release(&P.flags[F_OB + r * 8 + p], tag);
        TSTAMP(5);
      }
      __syncwarp();
    } else {
      uint32_t kn = 0, vm = 0, it = 0;
#pragma unroll 1
      for (int u = 0; u < 2; u++) {
        const unsigned long long* src = P.stats + (size_t)(p * 64 + lane * 2 + u) * 2;
        unsigned long long a, b;
        while (true) {
          asm volatile("ld.relaxed.gpu.global.u64 %0, [%1];" : "=l"(a) : "l"(src) : "memory");
          asm volatile("ld.relaxed.gpu.global.u64 %0, [%1];" : "=l"(b) : "l"(src + 1) : "memory");
          if ((unsigned)(a >> 32) == tag && (unsigned)(b >> 32) == tag) break;
          if (++it > SPIN_LIMIT) trap_now();
          __nanosleep(500);
        }
        kn = __vmaxu2(kn, (uint32_t)a);
        vm = __vmaxu2(vm, (uint32_t)b);
      }
#pragma unroll 1
      for (int o = 16; o; o >>= 1) {
        kn = __vmaxu2(kn, __shfl_xor_sync(0xffffffffu, kn, o));
        vm = __vmaxu2(vm, __shfl_xor_sync(0xffffffffu, vm, o));
      }
      if (elect()) {
        asm volatile("st.shared.v2.u32 [%0], {%1, %2};" ::"r"(sb + SM_STAT), "r"(kn), "r"(vm) : "memory");
        mbar_arrive(bar + 8 * B_STATS);
        mbar_expect(bar + 8 * B_FULLWOB, 7 * 16384);
#pragma unroll 1
        for (int c = 0; c < 7; c++) {
          mbar_wait(bar + 8 * (B_EMPTYXA + c), 0);
          tma_load(sb + SM_XA + c * 8192, &P.woB, cg * 112, c * 64, bar + 8 * B_FULLWOB);
          tma_load(sb + SM_XA + 57344 + c * 8192, &P.woB, cg * 112 + 48, c * 64, bar + 8 * B_FULLWOB);
        }
      }
      __syncwarp();
    }
  } else if (wg < 2) {
    if (OHALF && threadIdx.x < 96) {
      const int w = threadIdx.x & 31, row = w >> 2, col = (w & 3) * 2;
      const uint32_t v = (threadIdx.x >> 5) == 1 ? 0u : (row == col ? 0x00003c00u : (row == col + 1 ? 0x3c000000u : 0u));
      asm volatile("st.shared.u32 [%0], %1;" ::"r"(sb + SM_EYE + 4 * threadIdx.x), "r"(v) : "memory");
      fence_async_smem();
    }
    asm volatile("bar.sync 0, 512;" ::: "memory");
    asm volatile("barrier.cluster.arrive.relaxed.aligned;" ::: "memory");
    asm volatile("ld.volatile.global.u32 %0, [%1];" : "=r"(tag) : "l"(P.epoch));
    asm volatile("setmaxnreg.inc.sync.aligned.u32 168;");
    const int t = threadIdx.x & 127, g = lane >> 2, c4 = lane & 3;
    uint32_t qA[8], qB[8];
    const uint32_t empty_l = bar + 8 * B_EMPTYKV, empty_r = mapa(empty_l, rank ^ 1);
    asm volatile("barrier.cluster.wait.acquire.aligned;" ::: "memory");
    {
      float acc[64], aq[32];
      const uint32_t xd = desc_lo(sb + SM_XA + wg * 8192, 16), wd = desc_lo(sb, 8192) + (p & 1);
      const uint32_t emptyh_r = empty_r + 8 * (B_EMPTYH - B_EMPTYKV);
#pragma unroll 1
      for (int c = 0; c < 7; c++) {
        const uint32_t wc = wd + (head_slot(c < 5 ? c : c - 5) >> 4);
        mbar_wait(bar + 8 * (B_FULLH + c), 0);
        if (threadIdx.x == 0) TSTAMP(c ? 21 + c : 1);
        wg_fence();
#pragma unroll
        for (int kk = 0; kk < 4; kk++) mma_n128_ss_tb(acc, desc(xd + c * 1024 + kk * 2), desc(wc + kk * 128), kk ? 1 : c);
        wg_commit();
        wg_wait<1>();
        if (c == 1 && tag == 0) trap_now();
        mbar_arrive_if(bar + 8 * (B_EMPTYH - 1) + 8 * c, t == 0 && c > 0);
        mbar_arrive_cluster_if(emptyh_r - 8 + 8 * c, t == 32 && c > 0);
      }
      wg_wait<0>();
      pin(acc);
      if (threadIdx.x == 0) TSTAMP(2);
      auto q_chunk = [&](int c) {
        const uint32_t wc = wd + ((c < 6 ? head_slot(2) + c * 8192 : head_slot(0)) >> 4);
        mbar_wait(bar + 8 * (B_FULLQ + c), 0);
        wg_fence();
#pragma unroll
        for (int kk = 0; kk < 4; kk++) mma_n64_ss_tb(aq, desc(xd + c * 1024 + kk * 2), desc(wc + kk * 128), kk ? 1 : c);
        wg_commit();
      };
#pragma unroll
      for (int c = 0; c < QPRE; c++) q_chunk(c);
      const bool lo = c4 < 2;
      const int mrow = (lane & 7) + ((lane >> 3) & 1) * 8 + warp * 16;
      const uint32_t tile = sb + SM_KV + wg * 16384 + mrow * 128;
#pragma unroll
      for (int h = 0; h < 2; h++) {
#pragma unroll
        for (int ch = 0; ch < 8; ch += 2) {
          uint32_t v[4];
#pragma unroll
          for (int i = 0; i < 4; i++) {
            const int cc = ch + (i >> 1);
            const int b = (cc & 3) + 3 * h;
            const int a = (cc >> 2) * 32 + 4 * b + 2 * (i & 1);
            v[i] = pack_h(acc[a], acc[a + 1]);
            if (b == 3) {
              const uint32_t fill = (cc >= 4 && c4 == (h ? 0 : 2)) ? 0x00003c00u : 0u;
              v[i] = (lo == (h == 0)) ? v[i] : fill;
            }
          }
          stsm4(tile + h * 8192 + (((ch + (lane >> 4)) ^ (mrow & 7)) << 4), v[0], v[1], v[2], v[3]);
        }
      }
      fence_async_smem();
      __syncwarp();
      mbar_arrive_if(bar + 8 * B_OWNRDY, lane == 0);
#pragma unroll 1
      for (int c = QPRE; c < 7; c++) q_chunk(c);
      wg_wait<0>();
      pin(aq);
      mbar_arrive_if(bar + 8 * B_HEADDONE, t == 64);
      mbar_arrive_if(empty_l + 16, t == 0);
      mbar_arrive_if(empty_l + 24, t == 0);
      mbar_arrive_cluster_if(empty_r + 16, t == 32);
      mbar_arrive_cluster_if(empty_r + 24, t == 32);
#pragma unroll
      for (int i = 0; i < 8; i++) {
        const int a = 4 * (i >> 1) + 2 * (i & 1);
        qA[i] = pack_h(aq[a] * QSCALE, aq[a + 1] * QSCALE);
        qB[i] = pack_h(aq[12 + a] * QSCALE, aq[13 + a] * QSCALE);
      }
      if (!lo) qA[6] = qA[7] = 0;
      if (lo) qB[0] = qB[1] = 0;
    }
    float qn[2];
#pragma unroll
    for (int h = 0; h < 2; h++) {
      const uint32_t (&q)[8] = h ? qB : qA;
      uint32_t n0 = 0, n1 = 0;
#pragma unroll
      for (int i = 0; i < 4; i++) { n0 = hfma2(q[2 * i], q[2 * i], n0); n1 = hfma2(q[2 * i + 1], q[2 * i + 1], n1); }
      float a = h_lo(n0) + h_hi(n0), b = h_lo(n1) + h_hi(n1);
      a += __shfl_xor_sync(0xffffffffu, a, 1);
      b += __shfl_xor_sync(0xffffffffu, b, 1);
      a += __shfl_xor_sync(0xffffffffu, a, 2);
      b += __shfl_xor_sync(0xffffffffu, b, 2);
      qn[h] = __uint_as_float(max(__float_as_uint(a), __float_as_uint(b)));
    }
    mbar_wait(bar + 8 * B_OWNRDY, 0);
    if (threadIdx.x == 0) TSTAMP(3);

    float oA[16], oB[16];
    uint32_t sA[16], sB[16], pA[16], pB[16];
    uint32_t k0 = desc_lo(sb + SM_KV, 16), v0;
    const uint32_t zero = P.zero;
    uint32_t chain = 0x3c003c00u;
    uint32_t hA[8], hB[8];
    const uint64_t eye = (uint64_t)8 << 32 | desc_lo(sb + SM_EYE, 128);
    auto pv1 = [&](float (&o)[16], uint32_t (&h)[8], const uint32_t (&pp)[16], int kk, uint32_t vd, int acc) {
      if (OHALF) mma_pv_h(h, pp[4 * kk], pp[4 * kk + 1], pp[4 * kk + 2], pp[4 * kk + 3], desc(vd + kk * 128), acc);
      else mma_pv(o, pp[4 * kk], pp[4 * kk + 1], pp[4 * kk + 2], pp[4 * kk + 3], desc(vd + kk * 128), 1);
    };
    auto flush = [&](float (&o)[16], const uint32_t (&h)[8]) {
      if (OHALF) {
        mma_fl(*reinterpret_cast<float (*)[8]>(&o[0]), h[0], h[1], h[2], h[3], eye, 1);
        mma_fl(*reinterpret_cast<float (*)[8]>(&o[8]), h[4], h[5], h[6], h[7], eye, 1);
      }
    };
    auto pv_qk = [&](float (&o)[16], uint32_t (&h)[8], int acc, const uint32_t (&pp)[16], uint32_t vd, uint32_t (&s)[16],
                     const uint32_t (&q)[8], uint32_t kd) {
      if (WORD == 0) {
        pv1(o, h, pp, 0, vd, acc);
        if (QK0) mma_qk0(s, q[0], q[1], q[2], q[3], desc(kd)); else mma_qk(s, q[0], q[1], q[2], q[3], desc(kd), 0);
        pv1(o, h, pp, 1, vd, 1);
        mma_qk(s, q[4], q[5], q[6], q[7], desc(kd + 2), 1);
        pv1(o, h, pp, 2, vd, 1);
        pv1(o, h, pp, 3, vd, 1);
      } else if (WORD == 1) {
        pv1(o, h, pp, 0, vd, acc);
        pv1(o, h, pp, 1, vd, 1);
        if (QK0) mma_qk0(s, q[0], q[1], q[2], q[3], desc(kd)); else mma_qk(s, q[0], q[1], q[2], q[3], desc(kd), 0);
        pv1(o, h, pp, 2, vd, 1);
        mma_qk(s, q[4], q[5], q[6], q[7], desc(kd + 2), 1);
        pv1(o, h, pp, 3, vd, 1);
      } else {
        if (QK0) mma_qk0(s, q[0], q[1], q[2], q[3], desc(kd)); else mma_qk(s, q[0], q[1], q[2], q[3], desc(kd), 0);
        pv1(o, h, pp, 0, vd, acc);
        pv1(o, h, pp, 1, vd, 1);
        mma_qk(s, q[4], q[5], q[6], q[7], desc(kd + 2), 1);
        pv1(o, h, pp, 2, vd, 1);
        pv1(o, h, pp, 3, vd, 1);
      }
    };
#pragma unroll
    for (int i = 0; i < 16; i++) { oA[i] = oB[i] = 0.f; pB[i] = 0; hA[i >> 1] = hB[i >> 1] = 0; }
    pin(qA); pin(qB); pin(oA); pin(oB); pin(hA); pin(hB);
    wg_fence();
    mma_qk(sA, qA[0], qA[1], qA[2], qA[3], desc(k0), 0);
    mma_qk(sA, qA[4], qA[5], qA[6], qA[7], desc(k0 + 2), 1);
    wg_commit();
    wg_wait<0>();
    pin(sA);
    if (WOFF && wg == 1) { const long long c0 = clock64(); while (clock64() - c0 < WOFF) {} }
#pragma unroll 1
    for (int o = 0; o < 8; o++) {
      k0 = __shfl_sync(0xffffffffu, k0, 0);
      v0 = k0 + 4;
#pragma unroll
      for (int u = 0; u < 4; u++) {
        const uint32_t so = u * 1024, sp = ((u + 3) & 3) * 1024, sn = ((u + 1) & 3) * 1024;
        const uint32_t fbar = bar + 8 * (B_FULLKV + ((u + 1) & 3)), par = (u == 0 ? o + 1 : o) & 1;
        const bool nowait = (u == 0 && o == 0) || (u == 3 && o == 7);
        const uint32_t have = mbar_test(fbar, par) | nowait;
        pin(pB);
        wg_fence();
        pv_qk(oB, hB, u != 1, pB, v0 + 512 + (u == 0 && o == 0 ? 0 : sp), sB, qB, k0 + so + 512);
        if (u == 0) flush(oA, hA);
        wg_commit();
        if (BBK & 1) mbar_wait(fbar, par, zero + 1);
        exp_tile(sA, pA, zero, chain);
        pin(pA);
        wg_wait<0>();
        pin(sB); pin(oB); pin(sA); pin(hB); pin(oA);
        if (u == 1 || u == 2) mbar_wait(bar + 8 * (B_STOREDONE + u - 1), 0, o);
        mbar_wait(fbar, par, have);
        const bool rel = u == 0 ? o > 0 : (o < 7);
        mbar_arrive_if(empty_l + (sp >> 7), t == 0 && rel);
        mbar_arrive_cluster_if(empty_r + (sp >> 7), t == 32 && rel);
        wg_fence();
        pv_qk(oA, hA, u != 0, pA, v0 + so, sA, qA, k0 + sn);
        if (u == 0) flush(oB, hB);
        wg_commit();
        if (BBK & 2) mbar_wait(fbar, par, zero + 1);
        exp_tile(sB, pB, zero, chain);
        pin(pB);
        wg_wait<0>();
        pin(sA); pin(oA); pin(sB); pin(hA); pin(oB);
      }
    }
    wg_fence();
#pragma unroll
    for (int kk = 0; kk < 4; kk++) pv1(oB, hB, pB, kk, v0 + 3 * 1024 + 512, 1);
    flush(oA, hA);
    wg_commit();
    if (OHALF) {
      wg_wait<0>();
      pin(hB); pin(oA);
      wg_fence();
      flush(oB, hB);
      wg_commit();
    }
    if (threadIdx.x == 0) TSTAMP(29);
    mbar_wait(bar + 8 * B_STATS, 0);
    mbar_wait(bar + 8 * B_STGFREE, 0);
    uint32_t kn, vm;
    asm volatile("ld.shared.v2.u32 {%0, %1}, [%2];" : "=r"(kn), "=r"(vm) : "r"(sb + SM_STAT));
    bool ok = qn[0] * h_lo(kn) <= 1024.f && qn[1] * h_hi(kn) <= 1024.f && qn[0] <= 65504.f && qn[1] <= 65504.f &&
              h_lo(kn) <= 65504.f && h_hi(kn) <= 65504.f && h_lo(vm) <= 65504.f && h_hi(vm) <= 65504.f &&
              h_lo(vm) >= 0x1p-10f && h_hi(vm) >= 0x1p-10f && !P.force_slow;
    wg_wait<0>();
    pin(oB); pin(oA);
    if (threadIdx.x == 0) TSTAMP(4);
    mbar_arrive_if(bar + 8 * B_LOOPDONE, t == 0);
    {
      uint32_t v[14];
#pragma unroll
      for (int hr = 0; hr < 2; hr++) {
        const float lA = __shfl_sync(0xffffffffu, oA[12 + 2 * hr], (lane & ~3) | 2);
        const float lB = __shfl_sync(0xffffffffu, oB[2 * hr], lane & ~3);
        ok = ok && lA >= 128.f && lA < 16384.f && lB >= 128.f && lB < 16384.f &&
             (!OHALF || (lA * h_lo(vm) <= 60000.f && lB * h_hi(vm) <= 60000.f));
        const float iA = rcp_f(lA), iB = rcp_f(lB);
#pragma unroll
        for (int b = 0; b < 7; b++) {
          float a0, a1;
          if (b < 3) { a0 = oA[4 * b + 2 * hr] * iA; a1 = oA[4 * b + 2 * hr + 1] * iA; }
          else if (b > 3) { a0 = oB[4 * (b - 3) + 2 * hr] * iB; a1 = oB[4 * (b - 3) + 2 * hr + 1] * iB; }
          else if (c4 < 2) { a0 = oA[12 + 2 * hr] * iA; a1 = oA[13 + 2 * hr] * iA; }
          else { a0 = oB[2 * hr] * iB; a1 = oB[2 * hr + 1] * iB; }
          v[2 * b + hr] = pack_b(a0, a1);
        }
      }
      stage64(sb + SM_STG + wg * 8192 + warp * 2048, v, lane, p == 7);
      fence_async_smem();
    }
    if (__builtin_expect(named_or(2 + wg, 128, !ok), 0)) {
      mbar_wait(bar + 8 * B_LOOPDONE, 0);
      uint8_t* base = smem_raw + (sb - (uint32_t)__cvta_generic_to_shared(smem_raw));
      slow_attention(P.xBp, P.wBp, reinterpret_cast<float*>(base + SM_KV + wg * 32768),
                     reinterpret_cast<uint32_t*>(base + SM_STG + wg * 8192), r * 128 + wg * 64, p, t, 2 + wg);
      fence_async_smem();
      named_sync(2 + wg, 128);
    }
    if (threadIdx.x == 0) TSTAMP(28);
    mbar_arrive_if(bar + 8 * B_ATTNDONE, t == 0);
    {
      float o[28];
      const uint32_t od = desc_lo(sb + SM_KV, 16), wo = desc_lo(sb + SM_XA + wg * (57344 + 16), 16);
      mbar_wait(bar + 8 * B_FULLWOB, 0);
#pragma unroll 1
      for (int n = 0; n < 8; n++) {
        mbar_wait(bar + 8 * (B_FULLOB + n), 0);
        uint32_t c;
        asm volatile("ld.shared.u32 %0, [%1];" : "=r"(c) : "r"(sb + SM_ORDER + 4 * n) : "memory");
        const uint32_t wc = wo + __shfl_sync(0xffffffffu, c, 0);
        if (n == 0 && threadIdx.x == 0) TSTAMP(6);
        wg_fence();
#pragma unroll
        for (int kk = 0; kk < 4; kk++) mma_n56_ss_tb(o, desc(od + n * 512 + kk * 2), desc(wc + kk * 128), kk ? 1 : n);
        wg_commit();
      }
      wg_wait<0>();
      pin(o);
      uint32_t v[14];
#pragma unroll
      for (int i = 0; i < 14; i++) v[i] = pack_b(o[2 * i], o[2 * i + 1]);
      mbar_wait(bar + 8 * B_STGFREE, 1);
      stage56(sb + SM_STG + wg * 8192 + warp * (16 * 112), v, lane);
      fence_async_smem();
      named_sync(2 + wg, 128);
      if (t == 0) {
        tma_store(&P.outs, DM + cg * 112 + wg * 56, G * 64, sb + SM_STG + wg * 8192);
        bulk_commit();
        asm volatile("cp.async.bulk.wait_group 0;" ::: "memory");
      }
    }
    if (threadIdx.x == 0) { TSTAMP(7); GSTAMP(31); }
    if (cl == 0 && rank == 0 && threadIdx.x == 0) *(volatile unsigned*)P.epoch = tag + 1 ? tag + 1 : 1;
    if (threadIdx.x == 0) TDUMP();
  } else {
    asm volatile("bar.sync 0, 512;" ::: "memory");
    asm volatile("barrier.cluster.arrive.relaxed.aligned;" ::: "memory");
    asm volatile("ld.volatile.global.u32 %0, [%1];" : "=r"(tag) : "l"(P.epoch));
    asm volatile("setmaxnreg.inc.sync.aligned.u32 144;");
    const int t = threadIdx.x & 127, g = lane >> 2, c4 = lane & 3;
    auto kv_stats = [&]() {
    mbar_wait(bar + 8 * B_OWNRDY, 0);
    {
      uint32_t sk = 0, sv = 0;
#pragma unroll 1
      for (int h = 0; h < 2; h++) {
        const uint32_t rowa = sb + SM_KV + (t >> 6) * 16384 + h * 8192 + (t & 63) * 128;
        uint32_t n2 = 0, vm = 0;
#pragma unroll
        for (int ch = 0; ch < 8; ch++) {
          uint32_t v[4];
          asm volatile("ld.shared.v4.u32 {%0, %1, %2, %3}, [%4];" : "=r"(v[0]), "=r"(v[1]), "=r"(v[2]), "=r"(v[3])
                       : "r"(rowa + ((ch ^ (t & 7)) << 4)));
          if (ch == 7 && h == 0) v[2] = 0;
          if (ch == 4 && h == 1) v[0] = 0;
#pragma unroll
          for (int i = 0; i < 4; i++) {
            if (ch < 4) n2 = hfma2(v[i], v[i], n2);
            else vm = habsmax2(vm, v[i]);
          }
        }
        const uint32_t ns = __half_as_ushort(__float2half_rn(h_lo(n2) + h_hi(n2)));
        sk |= __reduce_max_sync(0xffffffffu, ns) << (16 * h);
        sv |= __reduce_max_sync(0xffffffffu, max(vm & 0xffffu, vm >> 16)) << (16 * h);
      }
      if (lane == 0) {
        mbar_arrive(bar + 8 * B_STOREDONE);
        unsigned long long* dst = P.stats + (size_t)(p * 64 + r * 4 + warp) * 2;
        const unsigned long long hi = (unsigned long long)tag << 32;
        asm volatile("st.relaxed.gpu.global.u64 [%0], %1;" ::"l"(dst), "l"(hi | sk) : "memory");
        asm volatile("st.relaxed.gpu.global.u64 [%0], %1;" ::"l"(dst + 1), "l"(hi | sv) : "memory");
      }
    }
      if (t == 0) TSTAMP(16);
    };
    mbar_wait(bar + 8 * B_HEADDONE, 0);
    kv_stats();
    if (!A_ON) {
      mbar_wait(bar + 8 * (B_FULLKV + 3), 0);
      if (t == 0) for (int c = 0; c < 7; c++) mbar_arrive(bar + 8 * (B_EMPTYXA + c));
    } else {
    const uint32_t xa = desc_lo(sb + SM_XA, 16), oa = desc_lo(sb + SM_WA, 16), wa = oa + (p & 1);
    {
      float acc[64];
#pragma unroll 1
      for (int n = 0; n < 14; n++) {
        const int c = (n == 0 || n == 7) ? 6 : (n < 7 ? n - 1 : n - 8);
        if (t == 0) ISTAMP(8 + n, clock());
        mbar_wait(bar + 8 * (B_FULLXA + c), 0, n >= 7);
        mbar_wait(bar + 8 * (B_FULLWA + (n & 3)), (n >> 2) & 1);
        if (t == 0) ISTAMP(72 + n, clock());
#pragma unroll
        for (int kk = 0; kk < 4; kk++) {
          if (kk % AGRP == 0) wg_fence();
          mma_n128_ss_ta(acc, desc(wa + (n & 3) * 512 + kk * 128), desc(xa + c * 1024 + kk * 2), kk ? 1 : c != 6);
          if (kk % AGRP == AGRP - 1) { wg_commit(); wg_wait<0>(); }
        }
        mbar_arrive_if(bar + 8 * (B_EMPTYWA + (n & 3)), t == 0);
        if (n == 6) {
          pin(acc);
          const int mrow = (lane & 7) + ((lane >> 3) & 1) * 8 + warp * 16;
          const uint32_t one = g == 0 ? 0x3f803f80u : 0u;
#pragma unroll
          for (int b = 0; b < 16; b += 2) {
            const int ch = (b & 7) + (lane >> 4);
            const uint32_t hi0 = pack_b(acc[4 * b + 2], acc[4 * b + 3]), hi1 = pack_b(acc[4 * b + 6], acc[4 * b + 7]);
            stsm4(sb + SM_STG + (b >> 3) * 8192 + mrow * 128 + ((ch ^ (mrow & 7)) << 4), pack_b(acc[4 * b], acc[4 * b + 1]),
                  warp == 3 ? one : hi0, pack_b(acc[4 * b + 4], acc[4 * b + 5]), warp == 3 ? one : hi1);
          }
          fence_async_smem();
          named_sync(1, 128);
        }
      }
      pin(acc);
      uint32_t pk[32];
#pragma unroll
      for (int i = 0; i < 32; i++) pk[i] = phi2(acc[2 * i], acc[2 * i + 1]);
      float kv[32];
      const uint32_t vt = desc_lo(sb + SM_STG, 16);
      pin(pk);
      if (t == 0) ISTAMP(96 + 15, clock());
#pragma unroll
      for (int kk = 0; kk < 8; kk++) {
        if (!(kk & 3)) wg_fence();
        mma_n64_rs(kv, pk[4 * kk], pk[4 * kk + 1], pk[4 * kk + 2], pk[4 * kk + 3], desc(vt + (kk >> 2) * 512 + (kk & 3) * 2), kk);
        if ((kk & 3) == 3) { wg_commit(); wg_wait<0>(); }
      }
      pin(kv);
      if (t == 0) ISTAMP(96 + 22, clock());
#pragma unroll
      for (int hr = 0; hr < 2; hr++) {
        const int dk = warp * 16 + hr * 8 + g;
        uint4* dst = P.part + (size_t)((p * 16 + r) * 56 + dk) * 32 + c4;
#pragma unroll
        for (int b = 0; b < 8; b++) {
          const int cp = 4 * b + c4;
          if (dk < 56 && (cp == 28 || (cp < 28 && (cp >= 14) == (dk >= DH))))
            asm volatile("st.relaxed.gpu.global.v4.u32 [%0], {%1, %2, %3, %3};" ::"l"(dst + 4 * b),
                         "r"(__float_as_uint(kv[4 * b + 2 * hr])), "r"(__float_as_uint(kv[4 * b + 2 * hr + 1])), "r"(tag) : "memory");
        }
      }
    }
    if (t == 0) TSTAMP(17);
    float q[2][32];
    const int dk = r * 4 + warp;
    const bool red_on = dk < 56 && (lane == 28 || (lane < 28 && (lane >= 14) == (dk >= DH)));
    const uint4* red_src = P.part + (size_t)(p * 16 * 56 + dk) * 32 + lane;
    uint4 v[8];
    float ra = 0.f, rb = 0.f;
    auto load8 = [&](const uint4* src, int stride) {
#pragma unroll
      for (int i = 0; i < 8; i++)
        asm volatile("ld.relaxed.gpu.global.v4.u32 {%0, %1, %2, %3}, [%4];" : "=r"(v[i].x), "=r"(v[i].y), "=r"(v[i].z), "=r"(v[i].w)
                     : "l"(src + (size_t)i * stride) : "memory");
    };
#pragma unroll 1
    for (int i = 0; i < 7; i++) {
      const int n = 14 + i, c = i ? i - 1 : 6;
      if (t == 0) ISTAMP(8 + n, clock());
      mbar_wait(bar + 8 * (B_FULLWA + (n & 3)), (n >> 2) & 1);
      if (t == 0) ISTAMP(72 + n, clock());
      if (i == 2 && red_on) load8(red_src, 56 * 32);
#pragma unroll
      for (int kk = 0; kk < 4; kk++) {
        const uint64_t bd = desc(wa + (n & 3) * 512 + kk * 128);
        if (kk % AGRP == 0) wg_fence();
        mma_n64_ss_tb(q[0], desc(xa + c * 1024 + kk * 2), bd, kk ? 1 : i);
        mma_n64_ss_tb(q[1], desc(xa + c * 1024 + 512 + kk * 2), bd, kk ? 1 : i);
        if (kk % AGRP == AGRP - 1) { wg_commit(); wg_wait<0>(); }
      }
      mbar_arrive_if(bar + 8 * (B_EMPTYWA + (n & 3)), t == 0);
      if (i == 3 || i == 5) {
        if (red_on) {
          uint32_t it = 0;
          while (true) {
            bool ok = true;
#pragma unroll
            for (int k = 0; k < 8; k++) ok = ok && v[k].z == tag;
            if (ok) break;
            if (++it > SPIN_LIMIT) trap_now();
            __nanosleep(300);
            load8(red_src, 56 * 32);
          }
#pragma unroll
          for (int k = 0; k < 8; k++) { ra += __uint_as_float(v[k].x); rb += __uint_as_float(v[k].y); }
          red_src += 8 * 56 * 32;
          if (i == 3) load8(red_src, 56 * 32);
        }
        __syncwarp();
        if (i == 5) {
          if (lane == 28) { if (dk >= DH) { rb = ra; ra = 0.f; } else rb = 0.f; }
          asm volatile("st.relaxed.gpu.global.v2.u32 [%0], {%1, %2};" ::"l"(P.kvf + (size_t)(p * 64 + dk) * 32 + lane),
                       "r"(pack_b(ra, rb)), "r"(tag) : "memory");
          if (t == 0) TSTAMP(21);
        }
      }
    }
    pin(q[0]);
    pin(q[1]);
    mbar_arrive_if(bar + 8 * B_XAFREE, t == 0);
    if (t == 0) ISTAMP(96 + 16, clock());
    uint32_t pq[2][16];
#pragma unroll
    for (int i = 0; i < 14; i++) pq[0][i] = phi2(q[0][2 * i], q[0][2 * i + 1]);
    const uint4* gsrc = reinterpret_cast<const uint4*>(P.kvf + (size_t)(p * 64 + warp * 16) * 32) + lane;
    if (t == 0) ISTAMP(96 + 17, clock());
    load8(gsrc, 32);
#pragma unroll
    for (int i = 0; i < 14; i++) pq[1][i] = phi2(q[1][2 * i], q[1][2 * i + 1]);
    pq[0][14] = pq[0][15] = pq[1][14] = pq[1][15] = 0;
    pin(pq[1]);
    if (t == 0) ISTAMP(96 + 18, clock());
    {
      uint32_t it = 0;
      while (true) {
        bool ok = true;
#pragma unroll
        for (int i = 0; i < 8; i++) ok = ok && v[i].y == tag && v[i].w == tag;
        if (ok) break;
        if (++it > SPIN_LIMIT) trap_now();
        __nanosleep(300);
        load8(gsrc, 32);
      }
      __syncwarp();
      if (t == 0) { ISTAMP(96 + 19, clock()); ISTAMP(96 + 23, it); }
#pragma unroll
      for (int i = 0; i < 8; i++) {
        const int row = warp * 16 + 2 * i + (lane >> 4);
        asm volatile("st.shared.v2.u32 [%0], {%1, %2};" ::"r"(sb + SM_STG + row * 128 + ((((lane & 15) >> 1) ^ (row & 7)) << 4) + (lane & 1) * 8),
                     "r"(v[i].x), "r"(v[i].z) : "memory");
      }
      fence_async_smem();
      named_sync(1, 128);
    }
    if (t == 0) ISTAMP(96 + 20, clock());
    {
      const uint32_t kd = desc_lo(sb + SM_STG, 16);
      pin(pq[0]);
      pin(pq[1]);
#pragma unroll
      for (int kk = 0; kk < 4; kk++) {
        if (!(kk & 1)) wg_fence();
        mma_n64_rs_tb(q[0], pq[0][4 * kk], pq[0][4 * kk + 1], pq[0][4 * kk + 2], pq[0][4 * kk + 3], desc(kd + kk * 128), kk);
        mma_n64_rs_tb(q[1], pq[1][4 * kk], pq[1][4 * kk + 1], pq[1][4 * kk + 2], pq[1][4 * kk + 3], desc(kd + kk * 128), kk);
        if (kk & 1) { wg_commit(); wg_wait<0>(); }
      }
      pin(q[0]);
      pin(q[1]);
      if (t == 0) ISTAMP(96 + 21, clock());
#pragma unroll
      for (int m = 0; m < 2; m++) {
        uint32_t v[14];
#pragma unroll
        for (int hr = 0; hr < 2; hr++) {
          const float i0 = rcp_f(__shfl_sync(0xffffffffu, q[m][28 + 2 * hr], lane & ~3) + 1e-6f);
          const float i1 = rcp_f(__shfl_sync(0xffffffffu, q[m][29 + 2 * hr], lane & ~3) + 1e-6f);
#pragma unroll
          for (int b = 0; b < 7; b++) {
            const float inv = b < 3 ? i0 : (b > 3 ? i1 : (c4 < 2 ? i0 : i1));
            v[2 * b + hr] = pack_b(q[m][4 * b + 2 * hr] * inv, q[m][4 * b + 2 * hr + 1] * inv);
          }
        }
        stage64(sb + SM_STG + m * 8192 + warp * 2048, v, lane, p == 7);
      }
      fence_async_smem();
      __syncwarp();
      mbar_arrive_if(bar + 8 * B_PUBA, lane == 0);
    }
    if (t == 0) TSTAMP(18);
    {
      float o[56];
      const uint32_t wo = desc_lo(sb + SM_XA, 57344);
#pragma unroll 1
      for (int i = 0; i < 7; i++) mbar_wait(bar + 8 * (B_FULLXA + i), 1);
      uint32_t done = 0;
#pragma unroll 1
      for (int i = 0; i < 8; i++) {
        const int n = 21 + i;
        if (t == 0 && i < 7) ISTAMP(56 + i, clock());
        mbar_wait(bar + 8 * (B_FULLWA + (n & 3)), (n >> 2) & 1);
        if (t == 0 && i < 7) ISTAMP(120 + i, clock());
        uint32_t c;
        asm volatile("ld.shared.u32 %0, [%1];" : "=r"(c) : "r"(sb + SM_ORDER + 32 + 4 * i) : "memory");
        c = __shfl_sync(0xffffffffu, c, 0);
        const uint32_t wc = wo + (c < 7 ? c * 448 : 3072);
#pragma unroll
        for (int kk = 0; kk < 4; kk++) {
          if (kk % AGRP == 0) wg_fence();
          mma_n112_ss_tb(o, desc(oa + (n & 3) * 512 + kk * 2), desc(wc + kk * 128), kk ? 1 : i);
          if (kk % AGRP == AGRP - 1) { wg_commit(); wg_wait<0>(); }
        }
        mbar_arrive_if(bar + 8 * (B_EMPTYWA + (n & 3)), t == 0);
        done |= 1u << c;
        mbar_arrive_if(bar + 8 * (B_EMPTYXA - 1) + 8 * c, t == 0 && ((done << 1) >> c & 1));
        mbar_arrive_if(bar + 8 * B_EMPTYXA + 8 * c, t == 32 && (done >> (c + 1) & 1));
      }
      pin(o);
#pragma unroll
      for (int m = 0; m < 2; m++) {
        uint32_t v[14];
#pragma unroll
        for (int i = 0; i < 14; i++) v[i] = pack_b(o[28 * m + 2 * i], o[28 * m + 2 * i + 1]);
        stage56(sb + SM_WA + m * 7168 + warp * (16 * 112), v, lane);
      }
      fence_async_smem();
      named_sync(1, 128);
      if (t == 0) {
        tma_store(&P.outs, cg * 112, G * 64, sb + SM_WA);
        tma_store(&P.outs, cg * 112 + 56, G * 64, sb + SM_WA + 7168);
        bulk_commit();
        asm volatile("cp.async.bulk.wait_group 0;" ::: "memory");
      }
    }
    if (t == 0) TSTAMP(19);
    }
  }
}

typedef CUresult (*EncodeFn)(CUtensorMap*, CUtensorMapDataType, cuuint32_t, void*, const cuuint64_t*, const cuuint64_t*,
                             const cuuint32_t*, const cuuint32_t*, CUtensorMapInterleave, CUtensorMapSwizzle,
                             CUtensorMapL2promotion, CUtensorMapFloatOOBfill);

void make_map(EncodeFn enc, CUtensorMap* m, const void* ptr, uint64_t rows, uint64_t cols, uint32_t box_rows,
              uint32_t box_cols = 64) {
  cuuint64_t dims[2] = {cols, rows};
  cuuint64_t strides[1] = {cols * 2};
  cuuint32_t box[2] = {box_cols, box_rows};
  cuuint32_t es[2] = {1, 1};
  enc(m, CU_TENSOR_MAP_DATA_TYPE_BFLOAT16, 2, const_cast<void*>(ptr), dims, strides, box, es,
      CU_TENSOR_MAP_INTERLEAVE_NONE, box_cols == 64 ? CU_TENSOR_MAP_SWIZZLE_128B : CU_TENSOR_MAP_SWIZZLE_NONE,
      CU_TENSOR_MAP_L2_PROMOTION_L2_128B,
      CU_TENSOR_MAP_FLOAT_OOB_FILL_NONE);
}

}

#define DEV_FORCE_SLOW 0

extern "C" void kernel_launch(void* const* d_in, const int* in_sizes, int n_in, void* d_out, int out_size) {
  static EncodeFn enc = nullptr;
  static void *kv, *oA, *oB, *kvf, *part, *stats, *flags, *epoch;
  if (!enc) {
    void* fn = nullptr;
    cudaDriverEntryPointQueryResult q;
    cudaGetDriverEntryPoint("cuTensorMapEncodeTiled", &fn, cudaEnableDefault, &q);
    enc = (EncodeFn)fn;
    cudaGetSymbolAddress(&kv, g_kv);
    cudaGetSymbolAddress(&oA, g_oA);
    cudaGetSymbolAddress(&oB, g_oB);
    cudaGetSymbolAddress(&kvf, g_kvf);
    cudaGetSymbolAddress(&part, g_part);
    cudaGetSymbolAddress(&stats, g_stats);
    cudaGetSymbolAddress(&flags, g_flags);
    cudaGetSymbolAddress(&epoch, g_epoch);
    cudaFuncSetAttribute(fused_kernel, cudaFuncAttributeMaxDynamicSharedMemorySize, SMEM_BYTES);
  }
  Params P;
  make_map(enc, &P.xA, d_in[0], S_LEN, DM, 128);
  make_map(enc, &P.wA, d_in[1], DM, 3 * DM, 64);
  make_map(enc, &P.woA, d_in[2], DM, DM, 64);
  make_map(enc, &P.xB, d_in[3], S_LEN, DM, 128);
  make_map(enc, &P.wBh, d_in[4], DM, 3 * DM, 32);
  make_map(enc, &P.woB, d_in[5], DM, DM, 64);
  make_map(enc, &P.kv, kv, 16 * S_LEN, 64, 64);
  make_map(enc, &P.oA, oA, S_LEN, 512, 64);
  make_map(enc, &P.oB, oB, S_LEN, 512, 64);
  make_map(enc, &P.outs, d_out, S_LEN, 2 * DM, 64, 56);
  P.xBp = (const __nv_bfloat16*)d_in[3];
  P.wBp = (const __nv_bfloat16*)d_in[4];
  P.part = (uint4*)part;
  P.kvf = (uint2*)kvf;
  P.stats = (unsigned long long*)stats;
  P.flags = (unsigned*)flags;
  P.epoch = (unsigned*)epoch;
  P.force_slow = DEV_FORCE_SLOW;
  P.zero = 0;
  fused_kernel<<<SMAP ? 132 : 128, 512, SMEM_BYTES>>>(P);
}
```

```cpp
#include <cuda_runtime.h>
#include <cuda_bf16.h>
#include <cuda_fp16.h>
#include <cuda.h>
#include <stdint.h>

namespace {

constexpr int S_LEN = 2048, DM = 448, DH = 28;
constexpr float QSCALE = 0.18898223650461362f * 1.4426950408889634f;

constexpr uint32_t SM_KV = 0;
constexpr uint32_t SM_XA = 65536;
constexpr uint32_t SM_WA = 180224;
constexpr uint32_t SM_STG = 212992;
constexpr uint32_t SM_BAR = 229376;
constexpr uint32_t SM_STAT = SM_BAR + 576;
constexpr uint32_t SM_ORDER = SM_STAT + 16;
constexpr uint32_t SM_EYE = SM_BAR + 1024;
constexpr uint32_t SMEM_BYTES = SM_BAR + 2048 + 1024;

__device__ __forceinline__ constexpr uint32_t head_slot(int i) { return i < 2 ? 32768 + i * 16384 : SM_WA + (i - 2) * 16384; }

enum {
  B_FULLH = 0, B_FULLKV = 7, B_EMPTYKV = 11, B_OWNRDY = 15, B_STOREDONE = 16  ,
  B_FULLXA = 18, B_FULLWA = 25, B_EMPTYWA = 29, B_XAFREE = 33, B_STGFREE = 34, B_STATS = 35, B_ATTNDONE = 36,
  B_FULLWOB = 37, B_LOOPDONE = 38, B_PUBA = 39, B_EMPTYXA = 40, B_FULLOB = 47, B_HEADDONE = 55, B_FULLQ = 56,
  B_EMPTYH = 63, B_COUNT = 69
};

enum { F_KV = 0, F_OA = 256, F_OB = 1280, F_COUNT = 2304 };
__device__ __align__(1024) __half g_kv[16 * S_LEN * 64];
__device__ __align__(1024) __nv_bfloat16 g_oA[S_LEN * 512];
__device__ __align__(1024) __nv_bfloat16 g_oB[S_LEN * 512];
__device__ __align__(1024) uint4 g_part[8 * 16 * 56 * 32];
__device__ __align__(1024) uint2 g_kvf[8 * 64 * 32];
__device__ __align__(1024) unsigned long long g_stats[8 * 64 * 2];
__device__ __align__(1024) unsigned g_flags[F_COUNT];
__device__ unsigned g_epoch = 1;

struct __align__(64) Params {
  CUtensorMap xB, wBh, xA, wA, woA, woB, kv, oA, oB;
  const __nv_bfloat16* xBp;
  const __nv_bfloat16* wBp;
  uint4* part;
  uint2* kvf;
  uint4 *oBp, *outp;
  unsigned long long* stats;
  unsigned* flags;
  unsigned* epoch;
  uint32_t zero;
};

constexpr uint32_t SPIN_LIMIT = 1u << 24;
constexpr int NPOLY = 5;

__device__ __forceinline__ void trap_now() { asm volatile("st.global.u32 [%0], %1;" ::"l"(0ull), "r"(0) : "memory"); }
__device__ __forceinline__ void mbar_init(uint32_t a, uint32_t c) {
  asm volatile("mbarrier.init.shared::cta.b64 [%0], %1;" ::"r"(a), "r"(c));
}
__device__ __forceinline__ void mbar_expect(uint32_t a, uint32_t bytes) {
  asm volatile("mbarrier.arrive.expect_tx.shared::cta.b64 _, [%0], %1;" ::"r"(a), "r"(bytes) : "memory");
}
__device__ __forceinline__ void mbar_arrive(uint32_t a) {
  asm volatile("mbarrier.arrive.shared::cta.b64 _, [%0];" ::"r"(a) : "memory");
}
__device__ __forceinline__ void mbar_arrive_if(uint32_t a, bool c) {
  asm volatile("{\n.reg .pred p;\nsetp.ne.b32 p, %1, 0;\n@p mbarrier.arrive.shared::cta.b64 _, [%0];\n}" ::"r"(a),
               "r"((uint32_t)c) : "memory");
}
__device__ __forceinline__ void mbar_arrive_cluster_if(uint32_t a, bool c) {
  asm volatile("{\n.reg .pred p;\nsetp.ne.b32 p, %1, 0;\n@p mbarrier.arrive.shared::cluster.b64 _, [%0];\n}" ::"r"(a),
               "r"((uint32_t)c) : "memory");
}
__device__ __forceinline__ uint32_t mbar_test(uint32_t a, uint32_t parity) {
  uint32_t ok;
  asm volatile("{\n.reg .pred p;\nmbarrier.test_wait.parity.shared::cta.b64 p, [%1], %2;\nselp.u32 %0, 1, 0, p;\n}"
               : "=r"(ok) : "r"(a), "r"(parity) : "memory");
  return ok;
}
__device__ __forceinline__ void mbar_wait_b(uint32_t a, uint32_t parity) {
  asm volatile(
      "{\n.reg .pred p;\n.reg .u32 n;\n.reg .u64 z;\nmov.u32 n, %2;\n"
      "SPIN:\nmbarrier.try_wait.parity.shared::cta.b64 p, [%0], %1;\n@p bra.uni DONE;\n"
      "sub.u32 n, n, 1;\nsetp.ne.u32 p, n, 0;\n@p bra.uni SPIN;\n"
      "mov.u64 z, 0;\nst.global.u32 [z], n;\nbra.uni SPIN;\nDONE:\n}"
      ::"r"(a), "r"(parity), "n"(SPIN_LIMIT) : "memory");
}
__device__ __forceinline__ void mbar_wait(uint32_t a, uint32_t parity, uint32_t have = 0) {
  asm volatile(
      "{\n.reg .pred p;\nsetp.ne.u32 p, %2, 0;\n@p bra.uni DONE;\n"
      "SPIN:\nmbarrier.try_wait.parity.shared::cta.b64 p, [%0], %1;\n@!p bra.uni SPIN;\nDONE:\n}"
      ::"r"(a), "r"(parity), "r"(have) : "memory");
}
__device__ __forceinline__ uint32_t mapa(uint32_t a, uint32_t rank) {
  uint32_t r;
  asm("mapa.shared::cluster.u32 %0, %1, %2;" : "=r"(r) : "r"(a), "r"(rank));
  return r;
}
__device__ __forceinline__ bool elect() {
  uint32_t p;
  asm volatile("{\n.reg .pred P;\nelect.sync _|P, 0xffffffff;\nselp.u32 %0, 1, 0, P;\n}" : "=r"(p));
  return p;
}
__device__ __forceinline__ void tma_load(uint32_t dst, const CUtensorMap* m, int c0, int c1, uint32_t bar) {
  asm volatile("cp.async.bulk.tensor.2d.shared::cluster.global.mbarrier::complete_tx::bytes [%0], [%1, {%3, %4}], [%2];"
               ::"r"(dst), "l"(m), "r"(bar), "r"(c0), "r"(c1) : "memory");
}
__device__ __forceinline__ void tma_load_mc(uint32_t dst, const CUtensorMap* m, int c0, int c1, uint32_t bar) {
  asm volatile(
      "cp.async.bulk.tensor.2d.shared::cluster.global.mbarrier::complete_tx::bytes.multicast::cluster [%0], [%1, {%3, %4}], [%2], %5;"
      ::"r"(dst), "l"(m), "r"(bar), "r"(c0), "r"(c1), "h"((uint16_t)3) : "memory");
}
__device__ __forceinline__ void tma_store(const CUtensorMap* m, int c0, int c1, uint32_t src) {
  asm volatile("cp.async.bulk.tensor.2d.global.shared::cta.bulk_group [%0, {%2, %3}], [%1];" ::"l"(m), "r"(src),
               "r"(c0), "r"(c1) : "memory");
}
__device__ __forceinline__ void tma_prefetch_l2(const CUtensorMap* m, int c0, int c1) {
  asm volatile("cp.async.bulk.prefetch.tensor.2d.L2.global [%0, {%1, %2}];" ::"l"(m), "r"(c0), "r"(c1) : "memory");
}
__device__ __forceinline__ void prefetch_map(const CUtensorMap* m) {
  asm volatile("prefetch.tensormap [%0];" ::"l"(m) : "memory");
}
__device__ __forceinline__ void fence_async_smem() { asm volatile("fence.proxy.async.shared::cta;" ::: "memory"); }
__device__ __forceinline__ void fence_async_all() { asm volatile("fence.proxy.async.global;" ::: "memory"); }
__device__ __forceinline__ void named_sync(int id, int n) { asm volatile("bar.sync %0, %1;" ::"r"(id), "r"(n) : "memory"); }
__device__ __forceinline__ bool named_or(int id, int n, bool v) {
  uint32_t r;
  asm volatile("{\n.reg .pred p, q;\nsetp.ne.b32 p, %3, 0;\nbarrier.red.or.pred q, %1, %2, p;\nselp.u32 %0, 1, 0, q;\n}"
               : "=r"(r) : "r"(id), "r"(n), "r"((uint32_t)v) : "memory");
  return r;
}
__device__ __forceinline__ unsigned ld_flag(const unsigned* p) {
  unsigned v;
  asm volatile("ld.relaxed.gpu.global.u32 %0, [%1];" : "=r"(v) : "l"(p) : "memory");
  return v;
}
__device__ __forceinline__ void bulk_commit() { asm volatile("cp.async.bulk.commit_group;" ::: "memory"); }
__device__ __forceinline__ void bulk_wait() {
  asm volatile("cp.async.bulk.wait_group 0;" ::: "memory");
  asm volatile("fence.proxy.async.global;" ::: "memory");
}
__device__ __forceinline__ void st_release(unsigned* p, unsigned v) {
  asm volatile("st.release.gpu.global.u32 [%0], %1;" ::"l"(p), "r"(v) : "memory");
}

__device__ __forceinline__ void wg_fence() { asm volatile("wgmma.fence.sync.aligned;" ::: "memory"); }
__device__ __forceinline__ void wg_commit() { asm volatile("wgmma.commit_group.sync.aligned;" ::: "memory"); }
template <int N> __device__ __forceinline__ void wg_wait() { asm volatile("wgmma.wait_group.sync.aligned %0;" ::"n"(N) : "memory"); }
template <int N> __device__ __forceinline__ void pin(float (&a)[N]) {
#pragma unroll
  for (int i = 0; i < N; i++) asm volatile("" : "+f"(a[i])::"memory");
}
template <int N> __device__ __forceinline__ void pin(uint32_t (&a)[N]) {
#pragma unroll
  for (int i = 0; i < N; i++) asm volatile("" : "+r"(a[i])::"memory");
}
__device__ __forceinline__ uint64_t desc(uint32_t lo) { return (uint64_t)0x40000040u << 32 | lo; }
__device__ __forceinline__ uint32_t desc_lo(uint32_t addr, uint32_t lbo) { return ((addr & 0x3FFFF) >> 4) | ((lbo >> 4) << 16); }

__device__ __forceinline__ void stsm4(uint32_t addr, uint32_t r0, uint32_t r1, uint32_t r2, uint32_t r3) {
  asm volatile("stmatrix.sync.aligned.m8n8.x4.shared.b16 [%0], {%1, %2, %3, %4};" ::"r"(addr), "r"(r0), "r"(r1),
               "r"(r2), "r"(r3) : "memory");
}
__device__ __forceinline__ void stsm2(uint32_t addr, uint32_t r0, uint32_t r1) {
  asm volatile("stmatrix.sync.aligned.m8n8.x2.shared.b16 [%0], {%1, %2};" ::"r"(addr), "r"(r0), "r"(r1) : "memory");
}
__device__ __forceinline__ void stage56(uint32_t base, const uint32_t (&v)[14], int lane) {
  const uint32_t a = base + (lane & 15) * 112 + (lane >> 4) * 16;
  stsm4(a, v[0], v[1], v[2], v[3]);
  stsm4(a + 32, v[4], v[5], v[6], v[7]);
  stsm4(a + 64, v[8], v[9], v[10], v[11]);
  stsm2(a + 96, v[12], v[13]);
}
__device__ __forceinline__ void stage64(uint32_t base, const uint32_t (&v)[14], int lane, int off) {
  const uint32_t a = base + (lane & 15) * 128, c = off + (lane >> 4), x = lane & 7;
  stsm4(a + ((c ^ x) << 4), v[0], v[1], v[2], v[3]);
  stsm4(a + (((c + 2) ^ x) << 4), v[4], v[5], v[6], v[7]);
  stsm4(a + (((c + 4) ^ x) << 4), v[8], v[9], v[10], v[11]);
  stsm4(a + ((((c + 6) & 7) ^ x) << 4), v[12], v[13], 0, 0);
}
__device__ __forceinline__ void copy_out(uint4* dst, uint32_t src, int lane) {
#pragma unroll
  for (int i = 0; i < 4; i++) {
    const int row = 4 * i + (lane >> 3);
    uint4 w;
    asm volatile("ld.shared.v4.u32 {%0, %1, %2, %3}, [%4];" : "=r"(w.x), "=r"(w.y), "=r"(w.z), "=r"(w.w)
                 : "r"(src + row * 128 + (((lane & 7) ^ (row & 7)) << 4)) : "memory");
    dst[row * 64 + (lane & 7)] = w;
  }
}
__device__ __forceinline__ void copy_out56(uint4* dst, uint32_t src, int lane) {
#pragma unroll
  for (int i = 0; i < 4; i++) {
    const int e = lane + 32 * i, row = (e * 147) >> 10;
    if (e < 112) {
      uint4 w;
      asm volatile("ld.shared.v4.u32 {%0, %1, %2, %3}, [%4];" : "=r"(w.x), "=r"(w.y), "=r"(w.z), "=r"(w.w) : "r"(src + e * 16) : "memory");
      dst[row * 112 + (e - 7 * row)] = w;
    }
  }
}
__device__ __forceinline__ uint32_t pack_h(float lo, float hi) {
  uint32_t r;
  asm("cvt.rn.f16x2.f32 %0, %1, %2;" : "=r"(r) : "f"(hi), "f"(lo));
  return r;
}
__device__ __forceinline__ uint32_t pack_b(float lo, float hi) {
  uint32_t r;
  asm("cvt.rn.bf16x2.f32 %0, %1, %2;" : "=r"(r) : "f"(hi), "f"(lo));
  return r;
}
__device__ __forceinline__ uint32_t ex2_h2(uint32_t x) {
  uint32_t y;
  asm("ex2.approx.f16x2 %0, %1;" : "=r"(y) : "r"(x));
  return y;
}
__device__ __forceinline__ float ex2_f(float x) {
  float y;
  asm("ex2.approx.ftz.f32 %0, %1;" : "=f"(y) : "f"(x));
  return y;
}
__device__ __forceinline__ float rcp_f(float x) {
  float y;
  asm("rcp.approx.f32 %0, %1;" : "=f"(y) : "f"(x));
  return y;
}
__device__ __forceinline__ uint32_t hfma2(uint32_t a, uint32_t b, uint32_t c) {
  uint32_t y;
  asm("fma.rn.f16x2 %0, %1, %2, %3;" : "=r"(y) : "r"(a), "r"(b), "r"(c));
  return y;
}
__device__ __forceinline__ uint32_t habsmax2(uint32_t m, uint32_t a) {
  uint32_t y;
  asm("max.f16x2 %0, %1, %2;" : "=r"(y) : "r"(m), "r"(a & 0x7fff7fffu));
  return y;
}
__device__ __forceinline__ float h_lo(uint32_t v) { return __half2float(__ushort_as_half((unsigned short)(v & 0xffff))); }
__device__ __forceinline__ float h_hi(uint32_t v) { return __half2float(__ushort_as_half((unsigned short)(v >> 16))); }
__device__ __forceinline__ uint32_t phi2(float a, float b) {
  const float ea = ex2_f(fminf(a * 1.4426950408889634f, 0.f)), eb = ex2_f(fminf(b * 1.4426950408889634f, 0.f));
  return pack_b(fmaxf(a, 0.f) + ea + 1e-6f, fmaxf(b, 0.f) + eb + 1e-6f);
}

__device__ __forceinline__ void mma_n128_ss_tb(float (&d)[64], uint64_t a, uint64_t b, int acc) {
  asm volatile("{\n.reg .pred p;\nsetp.ne.b32 p, %66, 0;\n"
    "wgmma.mma_async.sync.aligned.m64n128k16.f32.bf16.bf16 "
    "{%0,%1,%2,%3,%4,%5,%6,%7,%8,%9,%10,%11,%12,%13,%14,%15,%16,%17,%18,%19,%20,%21,%22,%23,%24,%25,%26,%27,%28,%29,%30,%31,%32,%33,%34,%35,%36,%37,%38,%39,%40,%41,%42,%43,%44,%45,%46,%47,%48,%49,%50,%51,%52,%53,%54,%55,%56,%57,%58,%59,%60,%61,%62,%63}, "
    "%64, %65, p, 1, 1, 0, 1;\n}\n"
    : "+f"(d[0]), "+f"(d[1]), "+f"(d[2]), "+f"(d[3]), "+f"(d[4]), "+f"(d[5]), "+f"(d[6]), "+f"(d[7]),
      "+f"(d[8]), "+f"(d[9]), "+f"(d[10]), "+f"(d[11]), "+f"(d[12]), "+f"(d[13]), "+f"(d[14]), "+f"(d[15]),
      "+f"(d[16]), "+f"(d[17]), "+f"(d[18]), "+f"(d[19]), "+f"(d[20]), "+f"(d[21]), "+f"(d[22]), "+f"(d[23]),
      "+f"(d[24]), "+f"(d[25]), "+f"(d[26]), "+f"(d[27]), "+f"(d[28]), "+f"(d[29]), "+f"(d[30]), "+f"(d[31]),
      "+f"(d[32]), "+f"(d[33]), "+f"(d[34]), "+f"(d[35]), "+f"(d[36]), "+f"(d[37]), "+f"(d[38]), "+f"(d[39]),
      "+f"(d[40]), "+f"(d[41]), "+f"(d[42]), "+f"(d[43]), "+f"(d[44]), "+f"(d[45]), "+f"(d[46]), "+f"(d[47]),
      "+f"(d[48]), "+f"(d[49]), "+f"(d[50]), "+f"(d[51]), "+f"(d[52]), "+f"(d[53]), "+f"(d[54]), "+f"(d[55]),
      "+f"(d[56]), "+f"(d[57]), "+f"(d[58]), "+f"(d[59]), "+f"(d[60]), "+f"(d[61]), "+f"(d[62]), "+f"(d[63])
    : "l"(a), "l"(b), "r"(acc));
}
__device__ __forceinline__ void mma_qk(uint32_t (&d)[16], uint32_t a0, uint32_t a1, uint32_t a2, uint32_t a3, uint64_t b, int acc) {
  asm volatile("{\n.reg .pred p;\nsetp.ne.b32 p, %21, 0;\n"
    "wgmma.mma_async.sync.aligned.m64n64k16.f16.f16.f16 "
    "{%0,%1,%2,%3,%4,%5,%6,%7,%8,%9,%10,%11,%12,%13,%14,%15}, "
    "{%16,%17,%18,%19}, %20, p, 1, 1, 0;\n}\n"
    : "+r"(d[0]), "+r"(d[1]), "+r"(d[2]), "+r"(d[3]), "+r"(d[4]), "+r"(d[5]), "+r"(d[6]), "+r"(d[7]),
      "+r"(d[8]), "+r"(d[9]), "+r"(d[10]), "+r"(d[11]), "+r"(d[12]), "+r"(d[13]), "+r"(d[14]), "+r"(d[15])
    : "r"(a0), "r"(a1), "r"(a2), "r"(a3), "l"(b), "r"(acc));
}
__device__ __forceinline__ void mma_qk0(uint32_t (&d)[16], uint32_t a0, uint32_t a1, uint32_t a2, uint32_t a3, uint64_t b) {
  asm volatile("{\n.reg .pred p;\nsetp.ne.b32 p, %21, 0;\n"
    "wgmma.mma_async.sync.aligned.m64n64k16.f16.f16.f16 "
    "{%0,%1,%2,%3,%4,%5,%6,%7,%8,%9,%10,%11,%12,%13,%14,%15}, "
    "{%16,%17,%18,%19}, %20, p, 1, 1, 0;\n}\n"
    : "=r"(d[0]), "=r"(d[1]), "=r"(d[2]), "=r"(d[3]), "=r"(d[4]), "=r"(d[5]), "=r"(d[6]), "=r"(d[7]),
      "=r"(d[8]), "=r"(d[9]), "=r"(d[10]), "=r"(d[11]), "=r"(d[12]), "=r"(d[13]), "=r"(d[14]), "=r"(d[15])
    : "r"(a0), "r"(a1), "r"(a2), "r"(a3), "l"(b), "n"(0));
}
__device__ __forceinline__ void mma_pv_h(uint32_t (&d)[8], uint32_t a0, uint32_t a1, uint32_t a2, uint32_t a3, uint64_t b, int acc) {
  asm volatile("{\n.reg .pred p;\nsetp.ne.b32 p, %13, 0;\n"
    "wgmma.mma_async.sync.aligned.m64n32k16.f16.f16.f16 "
    "{%0,%1,%2,%3,%4,%5,%6,%7}, "
    "{%8,%9,%10,%11}, %12, p, 1, 1, 1;\n}\n"
    : "+r"(d[0]), "+r"(d[1]), "+r"(d[2]), "+r"(d[3]), "+r"(d[4]), "+r"(d[5]), "+r"(d[6]), "+r"(d[7])
    : "r"(a0), "r"(a1), "r"(a2), "r"(a3), "l"(b), "r"(acc));
}
__device__ __forceinline__ void mma_fl(float (&d)[8], uint32_t a0, uint32_t a1, uint32_t a2, uint32_t a3, uint64_t b, int acc) {
  asm volatile("{\n.reg .pred p;\nsetp.ne.b32 p, %13, 0;\n"
    "wgmma.mma_async.sync.aligned.m64n16k16.f32.f16.f16 "
    "{%0,%1,%2,%3,%4,%5,%6,%7}, "
    "{%8,%9,%10,%11}, %12, p, 1, 1, 0;\n}\n"
    : "+f"(d[0]), "+f"(d[1]), "+f"(d[2]), "+f"(d[3]), "+f"(d[4]), "+f"(d[5]), "+f"(d[6]), "+f"(d[7])
    : "r"(a0), "r"(a1), "r"(a2), "r"(a3), "l"(b), "r"(acc));
}
__device__ __forceinline__ void mma_n128_ss_ta(float (&d)[64], uint64_t a, uint64_t b, int acc) {
  asm volatile("{\n.reg .pred p;\nsetp.ne.b32 p, %66, 0;\n"
    "wgmma.mma_async.sync.aligned.m64n128k16.f32.bf16.bf16 "
    "{%0,%1,%2,%3,%4,%5,%6,%7,%8,%9,%10,%11,%12,%13,%14,%15,%16,%17,%18,%19,%20,%21,%22,%23,%24,%25,%26,%27,%28,%29,%30,%31,%32,%33,%34,%35,%36,%37,%38,%39,%40,%41,%42,%43,%44,%45,%46,%47,%48,%49,%50,%51,%52,%53,%54,%55,%56,%57,%58,%59,%60,%61,%62,%63}, "
    "%64, %65, p, 1, 1, 1, 0;\n}\n"
    : "+f"(d[0]), "+f"(d[1]), "+f"(d[2]), "+f"(d[3]), "+f"(d[4]), "+f"(d[5]), "+f"(d[6]), "+f"(d[7]),
      "+f"(d[8]), "+f"(d[9]), "+f"(d[10]), "+f"(d[11]), "+f"(d[12]), "+f"(d[13]), "+f"(d[14]), "+f"(d[15]),
      "+f"(d[16]), "+f"(d[17]), "+f"(d[18]), "+f"(d[19]), "+f"(d[20]), "+f"(d[21]), "+f"(d[22]), "+f"(d[23]),
      "+f"(d[24]), "+f"(d[25]), "+f"(d[26]), "+f"(d[27]), "+f"(d[28]), "+f"(d[29]), "+f"(d[30]), "+f"(d[31]),
      "+f"(d[32]), "+f"(d[33]), "+f"(d[34]), "+f"(d[35]), "+f"(d[36]), "+f"(d[37]), "+f"(d[38]), "+f"(d[39]),
      "+f"(d[40]), "+f"(d[41]), "+f"(d[42]), "+f"(d[43]), "+f"(d[44]), "+f"(d[45]), "+f"(d[46]), "+f"(d[47]),
      "+f"(d[48]), "+f"(d[49]), "+f"(d[50]), "+f"(d[51]), "+f"(d[52]), "+f"(d[53]), "+f"(d[54]), "+f"(d[55]),
      "+f"(d[56]), "+f"(d[57]), "+f"(d[58]), "+f"(d[59]), "+f"(d[60]), "+f"(d[61]), "+f"(d[62]), "+f"(d[63])
    : "l"(a), "l"(b), "r"(acc));
}
__device__ __forceinline__ void mma_n64_rs(float (&d)[32], uint32_t a0, uint32_t a1, uint32_t a2, uint32_t a3, uint64_t b, int acc) {
  asm volatile("{\n.reg .pred p;\nsetp.ne.b32 p, %37, 0;\n"
    "wgmma.mma_async.sync.aligned.m64n64k16.f32.bf16.bf16 "
    "{%0,%1,%2,%3,%4,%5,%6,%7,%8,%9,%10,%11,%12,%13,%14,%15,%16,%17,%18,%19,%20,%21,%22,%23,%24,%25,%26,%27,%28,%29,%30,%31}, "
    "{%32,%33,%34,%35}, %36, p, 1, 1, 0;\n}\n"
    : "+f"(d[0]), "+f"(d[1]), "+f"(d[2]), "+f"(d[3]), "+f"(d[4]), "+f"(d[5]), "+f"(d[6]), "+f"(d[7]),
      "+f"(d[8]), "+f"(d[9]), "+f"(d[10]), "+f"(d[11]), "+f"(d[12]), "+f"(d[13]), "+f"(d[14]), "+f"(d[15]),
      "+f"(d[16]), "+f"(d[17]), "+f"(d[18]), "+f"(d[19]), "+f"(d[20]), "+f"(d[21]), "+f"(d[22]), "+f"(d[23]),
      "+f"(d[24]), "+f"(d[25]), "+f"(d[26]), "+f"(d[27]), "+f"(d[28]), "+f"(d[29]), "+f"(d[30]), "+f"(d[31])
    : "r"(a0), "r"(a1), "r"(a2), "r"(a3), "l"(b), "r"(acc));
}
__device__ __forceinline__ void mma_n64_rs_tb(float (&d)[32], uint32_t a0, uint32_t a1, uint32_t a2, uint32_t a3, uint64_t b, int acc) {
  asm volatile("{\n.reg .pred p;\nsetp.ne.b32 p, %37, 0;\n"
    "wgmma.mma_async.sync.aligned.m64n64k16.f32.bf16.bf16 "
    "{%0,%1,%2,%3,%4,%5,%6,%7,%8,%9,%10,%11,%12,%13,%14,%15,%16,%17,%18,%19,%20,%21,%22,%23,%24,%25,%26,%27,%28,%29,%30,%31}, "
    "{%32,%33,%34,%35}, %36, p, 1, 1, 1;\n}\n"
    : "+f"(d[0]), "+f"(d[1]), "+f"(d[2]), "+f"(d[3]), "+f"(d[4]), "+f"(d[5]), "+f"(d[6]), "+f"(d[7]),
      "+f"(d[8]), "+f"(d[9]), "+f"(d[10]), "+f"(d[11]), "+f"(d[12]), "+f"(d[13]), "+f"(d[14]), "+f"(d[15]),
      "+f"(d[16]), "+f"(d[17]), "+f"(d[18]), "+f"(d[19]), "+f"(d[20]), "+f"(d[21]), "+f"(d[22]), "+f"(d[23]),
      "+f"(d[24]), "+f"(d[25]), "+f"(d[26]), "+f"(d[27]), "+f"(d[28]), "+f"(d[29]), "+f"(d[30]), "+f"(d[31])
    : "r"(a0), "r"(a1), "r"(a2), "r"(a3), "l"(b), "r"(acc));
}
__device__ __forceinline__ void mma_n64_ss_tb(float (&d)[32], uint64_t a, uint64_t b, int acc) {
  asm volatile("{\n.reg .pred p;\nsetp.ne.b32 p, %34, 0;\n"
    "wgmma.mma_async.sync.aligned.m64n64k16.f32.bf16.bf16 "
    "{%0,%1,%2,%3,%4,%5,%6,%7,%8,%9,%10,%11,%12,%13,%14,%15,%16,%17,%18,%19,%20,%21,%22,%23,%24,%25,%26,%27,%28,%29,%30,%31}, "
    "%32, %33, p, 1, 1, 0, 1;\n}\n"
    : "+f"(d[0]), "+f"(d[1]), "+f"(d[2]), "+f"(d[3]), "+f"(d[4]), "+f"(d[5]), "+f"(d[6]), "+f"(d[7]),
      "+f"(d[8]), "+f"(d[9]), "+f"(d[10]), "+f"(d[11]), "+f"(d[12]), "+f"(d[13]), "+f"(d[14]), "+f"(d[15]),
      "+f"(d[16]), "+f"(d[17]), "+f"(d[18]), "+f"(d[19]), "+f"(d[20]), "+f"(d[21]), "+f"(d[22]), "+f"(d[23]),
      "+f"(d[24]), "+f"(d[25]), "+f"(d[26]), "+f"(d[27]), "+f"(d[28]), "+f"(d[29]), "+f"(d[30]), "+f"(d[31])
    : "l"(a), "l"(b), "r"(acc));
}
__device__ __forceinline__ void mma_n112_ss_tb(float (&d)[56], uint64_t a, uint64_t b, int acc) {
  asm volatile("{\n.reg .pred p;\nsetp.ne.b32 p, %58, 0;\n"
    "wgmma.mma_async.sync.aligned.m64n112k16.f32.bf16.bf16 "
    "{%0,%1,%2,%3,%4,%5,%6,%7,%8,%9,%10,%11,%12,%13,%14,%15,%16,%17,%18,%19,%20,%21,%22,%23,%24,%25,%26,%27,%28,%29,%30,%31,%32,%33,%34,%35,%36,%37,%38,%39,%40,%41,%42,%43,%44,%45,%46,%47,%48,%49,%50,%51,%52,%53,%54,%55}, "
    "%56, %57, p, 1, 1, 0, 1;\n}\n"
    : "+f"(d[0]), "+f"(d[1]), "+f"(d[2]), "+f"(d[3]), "+f"(d[4]), "+f"(d[5]), "+f"(d[6]), "+f"(d[7]),
      "+f"(d[8]), "+f"(d[9]), "+f"(d[10]), "+f"(d[11]), "+f"(d[12]), "+f"(d[13]), "+f"(d[14]), "+f"(d[15]),
      "+f"(d[16]), "+f"(d[17]), "+f"(d[18]), "+f"(d[19]), "+f"(d[20]), "+f"(d[21]), "+f"(d[22]), "+f"(d[23]),
      "+f"(d[24]), "+f"(d[25]), "+f"(d[26]), "+f"(d[27]), "+f"(d[28]), "+f"(d[29]), "+f"(d[30]), "+f"(d[31]),
      "+f"(d[32]), "+f"(d[33]), "+f"(d[34]), "+f"(d[35]), "+f"(d[36]), "+f"(d[37]), "+f"(d[38]), "+f"(d[39]),
      "+f"(d[40]), "+f"(d[41]), "+f"(d[42]), "+f"(d[43]), "+f"(d[44]), "+f"(d[45]), "+f"(d[46]), "+f"(d[47]),
      "+f"(d[48]), "+f"(d[49]), "+f"(d[50]), "+f"(d[51]), "+f"(d[52]), "+f"(d[53]), "+f"(d[54]), "+f"(d[55])
    : "l"(a), "l"(b), "r"(acc));
}
__device__ __forceinline__ void mma_n56_ss_tb(float (&d)[28], uint64_t a, uint64_t b, int acc) {
  asm volatile("{\n.reg .pred p;\nsetp.ne.b32 p, %30, 0;\n"
    "wgmma.mma_async.sync.aligned.m64n56k16.f32.bf16.bf16 "
    "{%0,%1,%2,%3,%4,%5,%6,%7,%8,%9,%10,%11,%12,%13,%14,%15,%16,%17,%18,%19,%20,%21,%22,%23,%24,%25,%26,%27}, "
    "%28, %29, p, 1, 1, 0, 1;\n}\n"
    : "+f"(d[0]), "+f"(d[1]), "+f"(d[2]), "+f"(d[3]), "+f"(d[4]), "+f"(d[5]), "+f"(d[6]), "+f"(d[7]),
      "+f"(d[8]), "+f"(d[9]), "+f"(d[10]), "+f"(d[11]), "+f"(d[12]), "+f"(d[13]), "+f"(d[14]), "+f"(d[15]),
      "+f"(d[16]), "+f"(d[17]), "+f"(d[18]), "+f"(d[19]), "+f"(d[20]), "+f"(d[21]), "+f"(d[22]), "+f"(d[23]),
      "+f"(d[24]), "+f"(d[25]), "+f"(d[26]), "+f"(d[27])
    : "l"(a), "l"(b), "r"(acc));
}


__device__ __forceinline__ uint32_t exp2_fma_h2(uint32_t x, uint32_t magic, uint32_t& chain) {
  uint32_t c, t, n, f;
  asm("min.xorsign.abs.f16x2 %0, %1, %2;" : "=r"(c) : "r"(x), "r"(0x4b004b00u));
  asm("add.rn.f16x2 %0, %1, %2;" : "=r"(t) : "r"(c), "r"(magic));
  asm("sub.rn.f16x2 %0, %1, %2;" : "=r"(n) : "r"(t), "r"(0x66006600u));
  asm("sub.rn.f16x2 %0, %1, %2;" : "=r"(f) : "r"(c), "r"(n));
  uint32_t q = hfma2(0x2af92af9u, f, 0x33be33beu);
  q = hfma2(q, f, 0x398c398cu);
  q = hfma2(q, f, 0x3c003c00u);
  chain = q;
  return q + (t << 10) - 0x01980000u;
}
__device__ __forceinline__ void exp_tile(const uint32_t (&s)[16], uint32_t (&p)[16], uint32_t zero, uint32_t& chain) {
#pragma unroll
  for (int i = 0; i < 16; i++) {
    if ((i + 1) * NPOLY / 16 != i * NPOLY / 16) p[i] = exp2_fma_h2(s[i], hfma2(chain, zero, 0x66006600u), chain);
    else p[i] = ex2_h2(s[i]);
  }
}

__device__ __forceinline__ void slow_project(const __nv_bfloat16* __restrict__ xrow, const __nv_bfloat16* __restrict__ wcol,
                                             float (&o)[DH]) {
#pragma unroll
  for (int d = 0; d < DH; d++) o[d] = 0.f;
#pragma unroll 1
  for (int k = 0; k < DM; k += 2) {
    __nv_bfloat162 xv = *reinterpret_cast<const __nv_bfloat162*>(xrow + k);
#pragma unroll
    for (int u = 0; u < 2; u++) {
      float x = u ? __high2float(xv) : __low2float(xv);
      const uint2* wp = reinterpret_cast<const uint2*>(wcol + (size_t)(k + u) * (3 * DM));
#pragma unroll
      for (int d = 0; d < DH / 4; d++) {
        uint2 w = __ldg(wp + d);
        o[4 * d + 0] = fmaf(x, __uint_as_float(w.x << 16), o[4 * d + 0]);
        o[4 * d + 1] = fmaf(x, __uint_as_float(w.x & 0xffff0000u), o[4 * d + 1]);
        o[4 * d + 2] = fmaf(x, __uint_as_float(w.y << 16), o[4 * d + 2]);
        o[4 * d + 3] = fmaf(x, __uint_as_float(w.y & 0xffff0000u), o[4 * d + 3]);
      }
    }
  }
#pragma unroll
  for (int d = 0; d < DH; d++) o[d] = __bfloat162float(__float2bfloat16(o[d]));
}

__device__ __forceinline__ void slow_attention(const __nv_bfloat16* __restrict__ x, const __nv_bfloat16* __restrict__ w,
                                            float* scratch, uint32_t* stage, int row0, int p, int t, int bar_id) {
  const int head = 2 * p + (t >> 6), row = row0 + (t & 63);
  float q[DH], acc[DH], tmp[DH];
  slow_project(x + (size_t)row * DM, w + head * DH, q);
  float m = -INFINITY, l = 0.f;
#pragma unroll
  for (int d = 0; d < DH; d++) acc[d] = 0.f;
  float* mine = scratch + t * (2 * DH + 1);
  const float* keys = scratch + (t >> 6) * 64 * (2 * DH + 1);
#pragma unroll 1
  for (int kb = 0; kb < S_LEN; kb += 64) {
#pragma unroll 1
    for (int part = 0; part < 2; part++) {
      slow_project(x + (size_t)(kb + (t & 63)) * DM, w + (part + 1) * DM + head * DH, tmp);
#pragma unroll
      for (int d = 0; d < DH; d++) mine[part * DH + d] = tmp[d];
    }
    named_sync(bar_id, 128);
#pragma unroll 1
    for (int j = 0; j < 64; j++) {
      const float* kr = keys + j * (2 * DH + 1);
      float s = 0.f;
#pragma unroll
      for (int d = 0; d < DH; d++) s = fmaf(q[d], kr[d], s);
      s = __bfloat162float(__float2bfloat16(__bfloat162float(__float2bfloat16(s)) * 0.18898223650461362f));
      float mn = fmaxf(m, s);
      float a = __expf(m - mn), pj = __expf(s - mn);
      l = l * a + pj;
#pragma unroll
      for (int d = 0; d < DH; d++) acc[d] = fmaf(pj, kr[DH + d], acc[d] * a);
      m = mn;
    }
    named_sync(bar_id, 128);
  }
  float r = rcp_f(l);
#pragma unroll
  for (int d = 0; d < DH; d += 2) {
    const int w = (p == 7) * 4 + (t >> 6) * 14 + (d >> 1);
    stage[(t & 63) * 32 + (((w >> 2) ^ (t & 7)) << 2) + (w & 3)] = pack_b(acc[d] * r, acc[d + 1] * r);
  }
}

__global__ void __cluster_dims__(2, 1, 1) __launch_bounds__(512, 1) fused_kernel(const __grid_constant__ Params P) {
  extern __shared__ uint8_t smem_raw[];
  const uint32_t sb = __shfl_sync(0xffffffffu, ((uint32_t)__cvta_generic_to_shared(smem_raw) + 1023) & ~1023u, 0);
  const uint32_t bar = sb + SM_BAR;
  const int wg = __shfl_sync(0xffffffffu, threadIdx.x >> 7, 0);
  const int warp = __shfl_sync(0xffffffffu, (threadIdx.x >> 5) & 3, 0);
  const int lane = threadIdx.x & 31;
  const int rank = blockIdx.x & 1;
  const int cb = blockIdx.x >> 1;
  const int cl = cb < 4 ? (4 + cb) * 8 : (cb < 36 ? cb - 4 : (4 + (cb - 36) / 7) * 8 + 1 + (cb - 36) % 7);
  const int ci = cl & 7;
  const int p = cl >> 3;
  const int r = 2 * ci + rank;
  const int G = 4 * ci + (p >> 1);
  const int cg = 2 * (p & 1) + rank;
  const int wcol = 56 * p - 8 * (p & 1);

  unsigned tag;
  if (threadIdx.x >= 384 && threadIdx.x < 416) {
    if (elect()) {
      const uint32_t fb = bar + 8 * B_FULLH;
#pragma unroll
      for (int c = 0; c < 3; c++) mbar_init(fb + 8 * c, 1);
      asm volatile("fence.mbarrier_init.release.cluster;" ::: "memory");
#pragma unroll
      for (int c = 0; c < 3; c++) {
        mbar_expect(fb + 8 * c, 32768);
        tma_load(sb + SM_XA + c * 16384, &P.xB, c * 64, r * 128, fb + 8 * c);
        if (c == 0) {
#pragma unroll
          for (int b = 0; b < 4; b++) tma_load(sb + head_slot(0) + b * 4096, &P.wBh, (1 + (b >> 1)) * DM + wcol, (b & 1) * 32, fb);
        }
      }
    }
    __syncwarp();
  }
  if (wg == 3) {
    asm volatile("setmaxnreg.dec.sync.aligned.u32 32;");
    if (warp == 0) {
      asm volatile("bar.arrive 0, 512;" ::: "memory");
    } else {
      if (elect()) {
#pragma unroll
        for (int w = 1; w < 4; w++) {
          if (warp == w) {
#pragma unroll
            for (int i = 2 + w; i < B_COUNT; i += 3) {
              uint32_t c = 1;
              if (i >= B_EMPTYH || (i >= B_EMPTYKV && i < B_EMPTYKV + 4) || i == B_PUBA) c = 4;
              if (i == B_OWNRDY || i == B_ATTNDONE) c = 8;
              if (i == B_STOREDONE) c = 5;
              if (i == B_LOOPDONE || i == B_HEADDONE) c = 2;
              mbar_init(bar + 8 * i, c);
            }
          }
        }
        asm volatile("fence.mbarrier_init.release.cluster;" ::: "memory");
      }
      __syncwarp();
      asm volatile("bar.sync 0, 512;" ::: "memory");
    }
    asm volatile("barrier.cluster.arrive.relaxed.aligned;" ::: "memory");
    asm volatile("ld.volatile.global.u32 %0, [%1];" : "=r"(tag) : "l"(P.epoch));
    if (warp == 0) {
      asm volatile("barrier.cluster.wait.acquire.aligned;" ::: "memory");
      if (elect()) {
#pragma unroll 1
        for (int c = 1; c < 7; c++) {
          if (c > 2) {
            mbar_expect(bar + 8 * (B_FULLH + c), 32768);
            tma_load(sb + SM_XA + c * 16384, &P.xB, c * 64, r * 128, bar + 8 * (B_FULLH + c));
          }
          if (c >= 5) mbar_wait_b(bar + 8 * (B_EMPTYH + c - 5), 0);
          const uint32_t st = sb + head_slot(c < 5 ? c : c - 5) + rank * 4096;
          tma_load_mc(st, &P.wBh, DM + wcol, c * 64 + rank * 32, bar + 8 * (B_FULLH + c));
          tma_load_mc(st + 8192, &P.wBh, 2 * DM + wcol, c * 64 + rank * 32, bar + 8 * (B_FULLH + c));
          if (c == 4) { prefetch_map(&P.kv); prefetch_map(&P.oB); }
        }
#pragma unroll 1
        for (int c = 0; c < 7; c++) {
          if (!(c & 1)) mbar_wait_b(bar + 8 * (B_EMPTYH + 2 + (c >> 1)), 0);
          mbar_expect(bar + 8 * (B_FULLQ + c), 8192);
          tma_load_mc(sb + (c < 6 ? head_slot(2) + c * 8192 : head_slot(0)) + rank * 4096, &P.wBh, wcol, c * 64 + rank * 32,
                      bar + 8 * (B_FULLQ + c));
        }
      }
      __syncwarp();
      uint32_t ready = 0, todo = ~(15u << (4 * ci));
#pragma unroll 1
      for (int j = 2; j < 32; j++) {
        const int s = j & 3;
        uint32_t it = 0;
        const uint32_t want = j < 30 ? todo : 1u << (2 * (r ^ 1) + (j & 1));
        while (!(ready & want)) {
          ready = __ballot_sync(0xffffffffu, ld_flag(&P.flags[F_KV + p * 32 + lane]) == tag);
          if (++it > SPIN_LIMIT) trap_now();
        }
        const uint32_t m = ready & want, hi = m >> (2 * r) << (2 * r);
        const int blk = __ffs(hi ? hi : m) - 1;
        todo &= ~(1u << blk);
        __syncwarp();
        if (elect()) {
          if (it) fence_async_all();
          const uint32_t fb = bar + 8 * (B_FULLKV + s);
          mbar_wait_b(bar + 8 * (B_EMPTYKV + s), ((j - 2) >> 2) & 1);
          mbar_expect(fb, 16384);
          if (j < 30) {
            tma_load_mc(sb + SM_KV + s * 16384 + rank * 8192, &P.kv, 0, (2 * p + rank) * S_LEN + blk * 64, fb);
          } else {
            tma_load(sb + SM_KV + s * 16384, &P.kv, 0, (2 * p) * S_LEN + blk * 64, fb);
            tma_load(sb + SM_KV + s * 16384 + 8192, &P.kv, 0, (2 * p + 1) * S_LEN + blk * 64, fb);
          }
        }
        __syncwarp();
      }
      if (elect()) mbar_wait_b(bar + 8 * B_ATTNDONE, 0);
      __syncwarp();
      uint32_t left = 0xff, it = 0;
      int n = 0;
#pragma unroll 1
      while (left) {
        uint32_t m = left & __ballot_sync(0xffffffffu, lane < 8 && ld_flag(&P.flags[F_OB + ((G >> 1) * 8 + lane) * 8]) == tag);
        if (++it > SPIN_LIMIT) trap_now();
        left &= ~m;
        if (m && elect()) {
          fence_async_all();
#pragma unroll 1
          for (int k = n; m; k++, m &= m - 1) {
            const int c = __ffs(m) - 1;
            asm volatile("st.shared.u32 [%0], %1;" ::"r"(sb + SM_ORDER + 4 * k), "r"(c < 7 ? c * 448 : 3072) : "memory");
            mbar_expect(bar + 8 * (B_FULLOB + k), 8192);
            tma_load(sb + SM_KV + k * 8192, &P.oB, c * 64, G * 64, bar + 8 * (B_FULLOB + k));
          }
        }
        __syncwarp();
        n = 8 - __popc(left);
      }
    } else if (warp == 1) {
      if (elect()) {
        prefetch_map(&P.xA);
        prefetch_map(&P.wA);
        mbar_wait_b(bar + 8 * (B_EMPTYH + 1), 0);
        if (tag == 0) trap_now();
        if (p < 7) tma_prefetch_l2(&P.xA, p * 64, r * 128);
#pragma unroll 1
        for (int b = 0; b < 3; b++) tma_prefetch_l2(&P.wA, (2 - b) * DM + wcol, (r % 7) * 64);
        prefetch_map(&P.woA);
        prefetch_map(&P.woB);
        prefetch_map(&P.oA);
        mbar_wait_b(bar + 8 * B_HEADDONE, 0);
        int c = 6, col = 2 * DM + wcol;
#pragma unroll 1
        for (int n = 0; n < 21; n++) {
          const int s = n & 3;
          if (n < 7) {
            if (n == 1) mbar_wait_b(bar + 8 * (B_FULLKV + 3), 0);
            if (n > 1) mbar_wait_b(bar + 8 * (B_FULLXA + n - 2), 0);
            mbar_expect(bar + 8 * (B_FULLXA + c), 16384);
            tma_load(sb + SM_XA + c * 16384, &P.xA, c * 64, r * 128, bar + 8 * (B_FULLXA + c));
          }
          if (n >= 4) mbar_wait_b(bar + 8 * (B_EMPTYWA + s), ((n >> 2) - 1) & 1);
          mbar_expect(bar + 8 * (B_FULLWA + s), 8192);
          tma_load(sb + SM_WA + s * 8192, &P.wA, col, c * 64, bar + 8 * (B_FULLWA + s));
          if (++c == 7) c = 0;
          if (c == 6) col -= DM;
        }
        mbar_wait_b(bar + 8 * B_XAFREE, 0);
#pragma unroll 1
        for (int n = 0; n < 7; n++) {
          const uint32_t fb = bar + 8 * (B_FULLXA + n);
          if (n >= 2) mbar_wait_b(fb - 16, 1);
          mbar_expect(fb, 16384);
          tma_load(sb + SM_XA + n * 8192, &P.woA, cg * 112, n * 64, fb);
          tma_load(sb + SM_XA + 57344 + n * 8192, &P.woA, cg * 112 + 64, n * 64, fb);
        }
      }
      __syncwarp();
      uint32_t left = 0xff, it = 0;
      int n = 21;
#pragma unroll 1
      while (left) {
        uint32_t m = left & __ballot_sync(0xffffffffu, lane < 8 && ld_flag(&P.flags[F_OA + ((G >> 1) * 8 + lane) * 8]) == tag);
        if (++it > SPIN_LIMIT) trap_now();
        left &= ~m;
        if (!m) { __nanosleep(200); continue; }
        if (elect()) {
          fence_async_all();
#pragma unroll 1
          for (int k = n; m; k++, m &= m - 1) {
            const int c = __ffs(m) - 1, s = k & 3;
            mbar_wait_b(bar + 8 * (B_EMPTYWA + s), ((k >> 2) - 1) & 1);
            asm volatile("st.shared.u32 [%0], %1;" ::"r"(sb + SM_ORDER + 32 + 4 * (k - 21)), "r"(c) : "memory");
            mbar_expect(bar + 8 * (B_FULLWA + s), 8192);
            tma_load(sb + SM_WA + s * 8192, &P.oA, c * 64, G * 64, bar + 8 * (B_FULLWA + s));
          }
        }
        __syncwarp();
        n = 29 - __popc(left);
      }
    } else if (warp == 2) {
      if (elect()) {
        mbar_wait_b(bar + 8 * B_OWNRDY, 0);
#pragma unroll 1
        for (int h = 0; h < 2; h++) {
          tma_store(&P.kv, 0, (2 * p) * S_LEN + r * 128 + h * 64, sb + SM_KV + h * 16384);
          tma_store(&P.kv, 0, (2 * p + 1) * S_LEN + r * 128 + h * 64, sb + SM_KV + h * 16384 + 8192);
          bulk_commit();
          bulk_wait();
          mbar_arrive(bar + 8 * (B_STOREDONE + h));
          st_release(&P.flags[F_KV + p * 32 + 2 * r + h], tag);
        }
        mbar_wait_b(bar + 8 * B_PUBA, 0);
        tma_store(&P.oA, 64 * p, r * 128, sb + SM_STG);
        tma_store(&P.oA, 64 * p, r * 128 + 64, sb + SM_STG + 8192);
        bulk_commit();
        bulk_wait();
        mbar_arrive(bar + 8 * B_STGFREE);
        st_release(&P.flags[F_OA + (r * 8 + p) * 8], tag);
        mbar_wait_b(bar + 8 * B_ATTNDONE, 0);
        st_release(&P.flags[F_OB + (r * 8 + p) * 8], tag);
      }
      __syncwarp();
    } else {
      uint32_t kn = 0, vm = 0, it = 0;
#pragma unroll 1
      for (int u = 0; u < 2; u++) {
        const unsigned long long* src = P.stats + (size_t)(p * 64 + lane * 2 + u) * 2;
        unsigned long long a, b;
        while (true) {
          asm volatile("ld.relaxed.gpu.global.u64 %0, [%1];" : "=l"(a) : "l"(src) : "memory");
          asm volatile("ld.relaxed.gpu.global.u64 %0, [%1];" : "=l"(b) : "l"(src + 1) : "memory");
          if ((unsigned)(a >> 32) == tag && (unsigned)(b >> 32) == tag) break;
          if (++it > SPIN_LIMIT) trap_now();
          __nanosleep(500);
        }
        kn = __vmaxu2(kn, (uint32_t)a);
        vm = __vmaxu2(vm, (uint32_t)b);
      }
#pragma unroll 1
      for (int o = 16; o; o >>= 1) {
        kn = __vmaxu2(kn, __shfl_xor_sync(0xffffffffu, kn, o));
        vm = __vmaxu2(vm, __shfl_xor_sync(0xffffffffu, vm, o));
      }
      if (elect()) {
        asm volatile("st.shared.v2.u32 [%0], {%1, %2};" ::"r"(sb + SM_STAT), "r"(kn), "r"(vm) : "memory");
        mbar_arrive(bar + 8 * B_STATS);
        mbar_expect(bar + 8 * B_FULLWOB, 7 * 16384);
#pragma unroll 1
        for (int c = 0; c < 7; c++) {
          mbar_wait_b(bar + 8 * (B_EMPTYXA + c), 0);
          tma_load(sb + SM_XA + c * 8192, &P.woB, cg * 112, c * 64, bar + 8 * B_FULLWOB);
          tma_load(sb + SM_XA + 57344 + c * 8192, &P.woB, cg * 112 + 48, c * 64, bar + 8 * B_FULLWOB);
        }
      }
      __syncwarp();
    }
  } else if (wg < 2) {
    if (threadIdx.x < 96) {
      const int w = threadIdx.x & 31, row = w >> 2, col = (w & 3) * 2;
      const uint32_t v = (threadIdx.x >> 5) == 1 ? 0u : (row == col ? 0x00003c00u : (row == col + 1 ? 0x3c000000u : 0u));
      asm volatile("st.shared.u32 [%0], %1;" ::"r"(sb + SM_EYE + 4 * threadIdx.x), "r"(v) : "memory");
      fence_async_smem();
    }
    asm volatile("bar.sync 0, 512;" ::: "memory");
    asm volatile("barrier.cluster.arrive.relaxed.aligned;" ::: "memory");
    asm volatile("ld.volatile.global.u32 %0, [%1];" : "=r"(tag) : "l"(P.epoch));
    asm volatile("setmaxnreg.inc.sync.aligned.u32 168;");
    const int t = threadIdx.x & 127, c4 = lane & 3;
    uint32_t qA[8], qB[8];
    const uint32_t empty_l = bar + 8 * B_EMPTYKV, empty_r = mapa(empty_l, rank ^ 1);
    asm volatile("barrier.cluster.wait.acquire.aligned;" ::: "memory");
    {
      float acc[64], aq[32];
      const uint32_t xd = desc_lo(sb + SM_XA + wg * 8192, 16), wd = desc_lo(sb, 8192) + (p & 1);
      const uint32_t emptyh_r = empty_r + 8 * (B_EMPTYH - B_EMPTYKV);
#pragma unroll 1
      for (int c = 0; c < 7; c++) {
        const uint32_t wc = wd + (head_slot(c < 5 ? c : c - 5) >> 4);
        mbar_wait(bar + 8 * (B_FULLH + c), 0);
        wg_fence();
#pragma unroll
        for (int kk = 0; kk < 4; kk++) mma_n128_ss_tb(acc, desc(xd + c * 1024 + kk * 2), desc(wc + kk * 128), kk ? 1 : c);
        wg_commit();
        wg_wait<1>();
        if (c == 1 && tag == 0) trap_now();
        mbar_arrive_if(bar + 8 * (B_EMPTYH - 1) + 8 * c, t == 0 && c > 0);
        mbar_arrive_cluster_if(emptyh_r - 8 + 8 * c, t == 32 && c > 0);
      }
      wg_wait<0>();
      pin(acc);
      const bool lo = c4 < 2;
      const int mrow = (lane & 7) + ((lane >> 3) & 1) * 8 + warp * 16;
      const uint32_t tile = sb + SM_KV + wg * 16384 + mrow * 128;
#pragma unroll
      for (int h = 0; h < 2; h++) {
#pragma unroll
        for (int ch = 0; ch < 8; ch += 2) {
          uint32_t v[4];
#pragma unroll
          for (int i = 0; i < 4; i++) {
            const int cc = ch + (i >> 1);
            const int b = (cc & 3) + 3 * h;
            const int a = (cc >> 2) * 32 + 4 * b + 2 * (i & 1);
            v[i] = pack_h(acc[a], acc[a + 1]);
            if (b == 3) {
              const uint32_t fill = (cc >= 4 && c4 == (h ? 0 : 2)) ? 0x00003c00u : 0u;
              v[i] = (lo == (h == 0)) ? v[i] : fill;
            }
          }
          stsm4(tile + h * 8192 + (((ch + (lane >> 4)) ^ (mrow & 7)) << 4), v[0], v[1], v[2], v[3]);
        }
      }
      fence_async_smem();
      __syncwarp();
      mbar_arrive_if(bar + 8 * B_OWNRDY, lane == 0);
#pragma unroll 1
      for (int c = 0; c < 7; c++) {
        const uint32_t wc = wd + ((c < 6 ? head_slot(2) + c * 8192 : head_slot(0)) >> 4);
        mbar_wait(bar + 8 * (B_FULLQ + c), 0);
        wg_fence();
#pragma unroll
        for (int kk = 0; kk < 4; kk++) mma_n64_ss_tb(aq, desc(xd + c * 1024 + kk * 2), desc(wc + kk * 128), kk ? 1 : c);
        wg_commit();
      }
      wg_wait<0>();
      pin(aq);
      mbar_arrive_if(bar + 8 * B_HEADDONE, t == 64);
      mbar_arrive_if(empty_l + 16, t == 0);
      mbar_arrive_if(empty_l + 24, t == 0);
      mbar_arrive_cluster_if(empty_r + 16, t == 32);
      mbar_arrive_cluster_if(empty_r + 24, t == 32);
#pragma unroll
      for (int i = 0; i < 8; i++) {
        const int a = 4 * (i >> 1) + 2 * (i & 1);
        qA[i] = pack_h(aq[a] * QSCALE, aq[a + 1] * QSCALE);
        qB[i] = pack_h(aq[12 + a] * QSCALE, aq[13 + a] * QSCALE);
      }
      if (!lo) qA[6] = qA[7] = 0;
      if (lo) qB[0] = qB[1] = 0;
    }
    mbar_wait(bar + 8 * B_OWNRDY, 0);

    float oA[16], oB[16];
    uint32_t sA[16], sB[16], pA[16], pB[16];
    uint32_t k0 = desc_lo(sb + SM_KV, 16), v0;
    const uint32_t zero = P.zero;
    uint32_t chain = 0x3c003c00u;
    uint32_t hA[8], hB[8];
    const uint64_t eye = (uint64_t)8 << 32 | desc_lo(sb + SM_EYE, 128);
    uint64_t dbase = desc(k0);
    auto desc = [&](uint32_t lo) { return dbase + (uint64_t)(lo - k0); };
    auto pv = [&](uint32_t (&h)[8], const uint32_t (&pp)[16], int kk, uint32_t vd, int acc) {
      mma_pv_h(h, pp[4 * kk], pp[4 * kk + 1], pp[4 * kk + 2], pp[4 * kk + 3], desc(vd + kk * 128), acc);
    };
    auto flush = [&](float (&o)[16], const uint32_t (&h)[8]) {
      mma_fl(*reinterpret_cast<float (*)[8]>(&o[0]), h[0], h[1], h[2], h[3], eye, 1);
      mma_fl(*reinterpret_cast<float (*)[8]>(&o[8]), h[4], h[5], h[6], h[7], eye, 1);
    };
    auto pv_qk = [&](uint32_t (&h)[8], int acc, const uint32_t (&pp)[16], uint32_t vd, uint32_t (&s)[16], const uint32_t (&q)[8],
                     uint32_t kd) {
      pv(h, pp, 0, vd, acc);
      mma_qk0(s, q[0], q[1], q[2], q[3], desc(kd));
      pv(h, pp, 1, vd, 1);
      mma_qk(s, q[4], q[5], q[6], q[7], desc(kd + 2), 1);
      pv(h, pp, 2, vd, 1);
      pv(h, pp, 3, vd, 1);
    };
#pragma unroll
    for (int i = 0; i < 16; i++) { oA[i] = oB[i] = 0.f; pB[i] = 0; hA[i >> 1] = hB[i >> 1] = 0; }
    pin(qA); pin(qB); pin(oA); pin(oB); pin(hA); pin(hB);
    wg_fence();
    mma_qk(sA, qA[0], qA[1], qA[2], qA[3], desc(k0), 0);
    mma_qk(sA, qA[4], qA[5], qA[6], qA[7], desc(k0 + 2), 1);
    wg_commit();
    float qn[2];
#pragma unroll
    for (int h = 0; h < 2; h++) {
      const uint32_t (&q)[8] = h ? qB : qA;
      uint32_t n0 = 0, n1 = 0;
#pragma unroll
      for (int i = 0; i < 4; i++) { n0 = hfma2(q[2 * i], q[2 * i], n0); n1 = hfma2(q[2 * i + 1], q[2 * i + 1], n1); }
      float a = h_lo(n0) + h_hi(n0), b = h_lo(n1) + h_hi(n1);
      a += __shfl_xor_sync(0xffffffffu, a, 1);
      b += __shfl_xor_sync(0xffffffffu, b, 1);
      a += __shfl_xor_sync(0xffffffffu, a, 2);
      b += __shfl_xor_sync(0xffffffffu, b, 2);
      qn[h] = __uint_as_float(max(__float_as_uint(a), __float_as_uint(b)));
    }
    wg_wait<0>();
    pin(sA);
#pragma unroll 1
    for (int o = 0; o < 8; o++) {
      k0 = __shfl_sync(0xffffffffu, k0, 0);
      v0 = k0 + 4;
      dbase = (uint64_t)(0x40000040u + __shfl_sync(0xffffffffu, zero, 0)) << 32 | k0;
#pragma unroll
      for (int u = 0; u < 4; u++) {
        const uint32_t so = u * 1024, sp = ((u + 3) & 3) * 1024, sn = ((u + 1) & 3) * 1024;
        const uint32_t fbar = bar + 8 * (B_FULLKV + ((u + 1) & 3)), par = (u == 0 ? o + 1 : o) & 1;
        const bool nowait = (u == 0 && o == 0) || (u == 3 && o == 7);
        const uint32_t have = mbar_test(fbar, par) | nowait;
        pin(pB);
        wg_fence();
        pv_qk(hB, u != 1, pB, v0 + 512 + (u == 0 && o == 0 ? 0 : sp), sB, qB, k0 + so + 512);
        if (u == 0) flush(oA, hA);
        wg_commit();
        exp_tile(sA, pA, zero, chain);
        pin(pA);
        wg_wait<0>();
        pin(sB); pin(oB); pin(sA); pin(hB); pin(oA);
        if (u == 1 || u == 2) mbar_wait(bar + 8 * (B_STOREDONE + u - 1), 0, o);
        mbar_wait(fbar, par, have);
        const bool rel = u == 0 ? o > 0 : (o < 7);
        mbar_arrive_if(empty_l + (sp >> 7), t == 0 && rel);
        mbar_arrive_cluster_if(empty_r + (sp >> 7), t == 32 && rel);
        wg_fence();
        pv_qk(hA, u != 0, pA, v0 + so, sA, qA, k0 + sn);
        if (u == 0) flush(oB, hB);
        wg_commit();
        exp_tile(sB, pB, zero, chain);
        pin(pB);
        wg_wait<0>();
        pin(sA); pin(oA); pin(sB); pin(hA); pin(oB);
      }
    }
    wg_fence();
#pragma unroll
    for (int kk = 0; kk < 4; kk++) pv(hB, pB, kk, v0 + 3 * 1024 + 512, 1);
    wg_commit();
#pragma unroll
    for (int i = 0; i < 8; i++) { oA[2 * i] += h_lo(hA[i]); oA[2 * i + 1] += h_hi(hA[i]); }
    mbar_wait(bar + 8 * B_STATS, 0);
    mbar_wait(bar + 8 * B_STGFREE, 0);
    uint32_t kn, vm;
    asm volatile("ld.shared.v2.u32 {%0, %1}, [%2];" : "=r"(kn), "=r"(vm) : "r"(sb + SM_STAT));
    bool ok = qn[0] * h_lo(kn) <= 1024.f && qn[1] * h_hi(kn) <= 1024.f && qn[0] <= 65504.f && qn[1] <= 65504.f &&
              h_lo(kn) <= 65504.f && h_hi(kn) <= 65504.f && h_lo(vm) <= 65504.f && h_hi(vm) <= 65504.f &&
              h_lo(vm) >= 0x1p-10f && h_hi(vm) >= 0x1p-10f;
    uint32_t v[14];
#pragma unroll
    for (int hr = 0; hr < 2; hr++) {
      const float l = __shfl_sync(0xffffffffu, oA[12 + 2 * hr], (lane & ~3) | 2);
      ok = ok && l >= 128.f && l < 16384.f && l * h_lo(vm) <= 60000.f;
      const float inv = rcp_f(l);
#pragma unroll
      for (int b = 0; b < 4; b++) v[2 * b + hr] = pack_b(oA[4 * b + 2 * hr] * inv, oA[4 * b + 2 * hr + 1] * inv);
    }
    pin(v);
    wg_wait<0>();
    pin(oB); pin(hB);
    mbar_arrive_if(bar + 8 * B_LOOPDONE, t == 0);
#pragma unroll
    for (int i = 0; i < 8; i++) { oB[2 * i] += h_lo(hB[i]); oB[2 * i + 1] += h_hi(hB[i]); }
#pragma unroll
    for (int hr = 0; hr < 2; hr++) {
      const float l = __shfl_sync(0xffffffffu, oB[2 * hr], lane & ~3);
      ok = ok && l >= 128.f && l < 16384.f && l * h_hi(vm) <= 60000.f;
      const float inv = rcp_f(l);
#pragma unroll
      for (int b = 0; b < 4; b++) {
        const uint32_t w = pack_b(oB[4 * b + 2 * hr] * inv, oB[4 * b + 2 * hr + 1] * inv);
        v[2 * (b + 3) + hr] = (b > 0 || c4 >= 2) ? w : v[6 + hr];
      }
    }
    stage64(sb + SM_STG + wg * 8192 + warp * 2048, v, lane, p == 7);
    if (__builtin_expect(named_or(2 + wg, 128, !ok), 0)) {
      mbar_wait(bar + 8 * B_LOOPDONE, 0);
      uint8_t* base = smem_raw + (sb - (uint32_t)__cvta_generic_to_shared(smem_raw));
      slow_attention(P.xBp, P.wBp, reinterpret_cast<float*>(base + SM_KV + wg * 32768),
                     reinterpret_cast<uint32_t*>(base + SM_STG + wg * 8192), r * 128 + wg * 64, p, t, 2 + wg);
      fence_async_smem();
      named_sync(2 + wg, 128);
    }
    copy_out(P.oBp + (size_t)(r * 128 + wg * 64 + warp * 16) * 64 + p * 8, sb + SM_STG + wg * 8192 + warp * 2048, lane);
    __syncwarp();
    mbar_arrive_if(bar + 8 * B_ATTNDONE, lane == 0);
    {
      float o[28];
      const uint32_t od = desc_lo(sb + SM_KV, 16), wo = desc_lo(sb + SM_XA + wg * (57344 + 16), 16);
      mbar_wait(bar + 8 * B_FULLWOB, 0);
#pragma unroll 1
      for (int n = 0; n < 8; n++) {
        mbar_wait(bar + 8 * (B_FULLOB + n), 0);
        uint32_t c;
        asm volatile("ld.shared.u32 %0, [%1];" : "=r"(c) : "r"(sb + SM_ORDER + 4 * n) : "memory");
        const uint32_t wc = wo + __shfl_sync(0xffffffffu, c, 0);
        wg_fence();
#pragma unroll
        for (int kk = 0; kk < 4; kk++) mma_n56_ss_tb(o, desc(od + n * 512 + kk * 2), desc(wc + kk * 128), kk ? 1 : n);
        wg_commit();
      }
      wg_wait<0>();
      pin(o);
      uint32_t v[14];
#pragma unroll
      for (int i = 0; i < 14; i++) v[i] = pack_b(o[2 * i], o[2 * i + 1]);
      stage56(sb + SM_STG + wg * 8192 + warp * (16 * 112), v, lane);
      __syncwarp();
      copy_out56(P.outp + (size_t)(G * 64 + warp * 16) * 112 + 56 + cg * 14 + wg * 7, sb + SM_STG + wg * 8192 + warp * (16 * 112), lane);
    }
    if (cl == 0 && rank == 0 && threadIdx.x == 0) *(volatile unsigned*)P.epoch = tag + 1 ? tag + 1 : 1;
  } else {
    asm volatile("bar.sync 0, 512;" ::: "memory");
    asm volatile("barrier.cluster.arrive.relaxed.aligned;" ::: "memory");
    asm volatile("ld.volatile.global.u32 %0, [%1];" : "=r"(tag) : "l"(P.epoch));
    asm volatile("setmaxnreg.inc.sync.aligned.u32 144;");
    const int t = threadIdx.x & 127, g = lane >> 2, c4 = lane & 3;
    mbar_wait(bar + 8 * B_HEADDONE, 0);
    mbar_wait(bar + 8 * B_OWNRDY, 0);
    {
      uint32_t sk = 0, sv = 0;
#pragma unroll 1
      for (int h = 0; h < 2; h++) {
        const uint32_t rowa = sb + SM_KV + (t >> 6) * 16384 + h * 8192 + (t & 63) * 128;
        uint32_t n2 = 0, vm = 0;
#pragma unroll
        for (int ch = 0; ch < 8; ch++) {
          uint32_t v[4];
          asm volatile("ld.shared.v4.u32 {%0, %1, %2, %3}, [%4];" : "=r"(v[0]), "=r"(v[1]), "=r"(v[2]), "=r"(v[3])
                       : "r"(rowa + ((ch ^ (t & 7)) << 4)));
          if (ch == 7 && h == 0) v[2] = 0;
          if (ch == 4 && h == 1) v[0] = 0;
#pragma unroll
          for (int i = 0; i < 4; i++) {
            if (ch < 4) n2 = hfma2(v[i], v[i], n2);
            else vm = habsmax2(vm, v[i]);
          }
        }
        const uint32_t ns = __half_as_ushort(__float2half_rn(h_lo(n2) + h_hi(n2)));
        sk |= __reduce_max_sync(0xffffffffu, ns) << (16 * h);
        sv |= __reduce_max_sync(0xffffffffu, max(vm & 0xffffu, vm >> 16)) << (16 * h);
      }
      if (lane == 0) {
        mbar_arrive(bar + 8 * B_STOREDONE);
        unsigned long long* dst = P.stats + (size_t)(p * 64 + r * 4 + warp) * 2;
        const unsigned long long hi = (unsigned long long)tag << 32;
        asm volatile("st.relaxed.gpu.global.u64 [%0], %1;" ::"l"(dst), "l"(hi | sk) : "memory");
        asm volatile("st.relaxed.gpu.global.u64 [%0], %1;" ::"l"(dst + 1), "l"(hi | sv) : "memory");
      }
    }
    const uint32_t xa = desc_lo(sb + SM_XA, 16), oa = desc_lo(sb + SM_WA, 16), wa = oa + (p & 1);
    {
      float acc[64];
#pragma unroll 1
      for (int n = 0; n < 14; n++) {
        const int c = (n == 0 || n == 7) ? 6 : (n < 7 ? n - 1 : n - 8);
        mbar_wait(bar + 8 * (B_FULLXA + c), 0, n >= 7);
        mbar_wait(bar + 8 * (B_FULLWA + (n & 3)), (n >> 2) & 1);
#pragma unroll
        for (int kk = 0; kk < 4; kk++) {
          if (!(kk & 1)) wg_fence();
          mma_n128_ss_ta(acc, desc(wa + (n & 3) * 512 + kk * 128), desc(xa + c * 1024 + kk * 2), kk ? 1 : c != 6);
          if (kk & 1) { wg_commit(); wg_wait<0>(); }
        }
        mbar_arrive_if(bar + 8 * (B_EMPTYWA + (n & 3)), t == 0);
        if (n == 6) {
          pin(acc);
          const int mrow = (lane & 7) + ((lane >> 3) & 1) * 8 + warp * 16;
          const uint32_t one = g == 0 ? 0x3f803f80u : 0u;
#pragma unroll
          for (int b = 0; b < 16; b += 2) {
            const int ch = (b & 7) + (lane >> 4);
            const uint32_t hi0 = pack_b(acc[4 * b + 2], acc[4 * b + 3]), hi1 = pack_b(acc[4 * b + 6], acc[4 * b + 7]);
            stsm4(sb + SM_STG + (b >> 3) * 8192 + mrow * 128 + ((ch ^ (mrow & 7)) << 4), pack_b(acc[4 * b], acc[4 * b + 1]),
                  warp == 3 ? one : hi0, pack_b(acc[4 * b + 4], acc[4 * b + 5]), warp == 3 ? one : hi1);
          }
          fence_async_smem();
          named_sync(1, 128);
        }
      }
      pin(acc);
      uint32_t pk[32];
#pragma unroll
      for (int i = 0; i < 32; i++) pk[i] = phi2(acc[2 * i], acc[2 * i + 1]);
      float kv[32];
      const uint32_t vt = desc_lo(sb + SM_STG, 16);
      pin(pk);
#pragma unroll
      for (int kk = 0; kk < 8; kk++) {
        if (!(kk & 3)) wg_fence();
        mma_n64_rs(kv, pk[4 * kk], pk[4 * kk + 1], pk[4 * kk + 2], pk[4 * kk + 3], desc(vt + (kk >> 2) * 512 + (kk & 3) * 2), kk);
        if ((kk & 3) == 3) { wg_commit(); wg_wait<0>(); }
      }
      pin(kv);
#pragma unroll
      for (int hr = 0; hr < 2; hr++) {
        const int dk = warp * 16 + hr * 8 + g;
        uint4* dst = P.part + (size_t)((p * 16 + r) * 56 + dk) * 32 + c4;
#pragma unroll
        for (int b = 0; b < 8; b++) {
          const int cp = 4 * b + c4;
          if (dk < 56 && (cp == 28 || (cp < 28 && (cp >= 14) == (dk >= DH))))
            asm volatile("st.relaxed.gpu.global.v4.u32 [%0], {%1, %2, %3, %3};" ::"l"(dst + 4 * b),
                         "r"(__float_as_uint(kv[4 * b + 2 * hr])), "r"(__float_as_uint(kv[4 * b + 2 * hr + 1])), "r"(tag) : "memory");
        }
      }
    }
    float q[2][32];
    const int dk = r * 4 + warp;
    const bool red_on = dk < 56 && (lane == 28 || (lane < 28 && (lane >= 14) == (dk >= DH)));
    const uint4* red_src = P.part + (size_t)(p * 16 * 56 + dk) * 32 + lane;
    uint4 v[8];
    float ra = 0.f, rb = 0.f;
    auto load8 = [&](const uint4* src, int stride) {
#pragma unroll
      for (int i = 0; i < 8; i++)
        asm volatile("ld.relaxed.gpu.global.v4.u32 {%0, %1, %2, %3}, [%4];" : "=r"(v[i].x), "=r"(v[i].y), "=r"(v[i].z), "=r"(v[i].w)
                     : "l"(src + (size_t)i * stride) : "memory");
    };
#pragma unroll 1
    for (int i = 0; i < 7; i++) {
      const int n = 14 + i, c = i ? i - 1 : 6;
      mbar_wait(bar + 8 * (B_FULLWA + (n & 3)), (n >> 2) & 1);
      if (i == 2 && red_on) load8(red_src, 56 * 32);
#pragma unroll
      for (int kk = 0; kk < 4; kk++) {
        const uint64_t bd = desc(wa + (n & 3) * 512 + kk * 128);
        if (!(kk & 1)) wg_fence();
        mma_n64_ss_tb(q[0], desc(xa + c * 1024 + kk * 2), bd, kk ? 1 : i);
        mma_n64_ss_tb(q[1], desc(xa + c * 1024 + 512 + kk * 2), bd, kk ? 1 : i);
        if (kk & 1) { wg_commit(); wg_wait<0>(); }
      }
      mbar_arrive_if(bar + 8 * (B_EMPTYWA + (n & 3)), t == 0);
      if (i == 3 || i == 5) {
        if (red_on) {
          uint32_t it = 0;
          while (true) {
            bool ok = true;
#pragma unroll
            for (int k = 0; k < 8; k++) ok = ok && v[k].z == tag;
            if (ok) break;
            if (++it > SPIN_LIMIT) trap_now();
            __nanosleep(300);
            load8(red_src, 56 * 32);
          }
#pragma unroll
          for (int k = 0; k < 8; k++) { ra += __uint_as_float(v[k].x); rb += __uint_as_float(v[k].y); }
          red_src += 8 * 56 * 32;
          if (i == 3) load8(red_src, 56 * 32);
        }
        __syncwarp();
        if (i == 5) {
          if (lane == 28) { if (dk >= DH) { rb = ra; ra = 0.f; } else rb = 0.f; }
          asm volatile("st.relaxed.gpu.global.v2.u32 [%0], {%1, %2};" ::"l"(P.kvf + (size_t)(p * 64 + dk) * 32 + lane),
                       "r"(pack_b(ra, rb)), "r"(tag) : "memory");
        }
      }
    }
    pin(q[0]);
    pin(q[1]);
    mbar_arrive_if(bar + 8 * B_XAFREE, t == 0);
    uint32_t pq[2][16];
#pragma unroll
    for (int i = 0; i < 14; i++) pq[0][i] = phi2(q[0][2 * i], q[0][2 * i + 1]);
    const uint4* gsrc = reinterpret_cast<const uint4*>(P.kvf + (size_t)(p * 64 + warp * 16) * 32) + lane;
    load8(gsrc, 32);
#pragma unroll
    for (int i = 0; i < 14; i++) pq[1][i] = phi2(q[1][2 * i], q[1][2 * i + 1]);
    pq[0][14] = pq[0][15] = pq[1][14] = pq[1][15] = 0;
    pin(pq[1]);
    {
      uint32_t it = 0;
      while (true) {
        bool ok = true;
#pragma unroll
        for (int i = 0; i < 8; i++) ok = ok && v[i].y == tag && v[i].w == tag;
        if (ok) break;
        if (++it > SPIN_LIMIT) trap_now();
        __nanosleep(300);
        load8(gsrc, 32);
      }
      __syncwarp();
#pragma unroll
      for (int i = 0; i < 8; i++) {
        const int row = warp * 16 + 2 * i + (lane >> 4);
        asm volatile("st.shared.v2.u32 [%0], {%1, %2};" ::"r"(sb + SM_STG + row * 128 + ((((lane & 15) >> 1) ^ (row & 7)) << 4) + (lane & 1) * 8),
                     "r"(v[i].x), "r"(v[i].z) : "memory");
      }
      fence_async_smem();
      named_sync(1, 128);
    }
    {
      const uint32_t kd = desc_lo(sb + SM_STG, 16);
      pin(pq[0]);
      pin(pq[1]);
#pragma unroll
      for (int kk = 0; kk < 4; kk++) {
        if (!(kk & 1)) wg_fence();
        mma_n64_rs_tb(q[0], pq[0][4 * kk], pq[0][4 * kk + 1], pq[0][4 * kk + 2], pq[0][4 * kk + 3], desc(kd + kk * 128), kk);
        mma_n64_rs_tb(q[1], pq[1][4 * kk], pq[1][4 * kk + 1], pq[1][4 * kk + 2], pq[1][4 * kk + 3], desc(kd + kk * 128), kk);
        if (kk & 1) { wg_commit(); wg_wait<0>(); }
      }
      pin(q[0]);
      pin(q[1]);
#pragma unroll
      for (int m = 0; m < 2; m++) {
        uint32_t v[14];
#pragma unroll
        for (int hr = 0; hr < 2; hr++) {
          const float i0 = rcp_f(__shfl_sync(0xffffffffu, q[m][28 + 2 * hr], lane & ~3) + 1e-6f);
          const float i1 = rcp_f(__shfl_sync(0xffffffffu, q[m][29 + 2 * hr], lane & ~3) + 1e-6f);
#pragma unroll
          for (int b = 0; b < 7; b++) {
            const float inv = b < 3 ? i0 : (b > 3 ? i1 : (c4 < 2 ? i0 : i1));
            v[2 * b + hr] = pack_b(q[m][4 * b + 2 * hr] * inv, q[m][4 * b + 2 * hr + 1] * inv);
          }
        }
        stage64(sb + SM_STG + m * 8192 + warp * 2048, v, lane, p == 7);
      }
      fence_async_smem();
      __syncwarp();
      mbar_arrive_if(bar + 8 * B_PUBA, lane == 0);
    }
    {
      float o[56];
      const uint32_t wo = desc_lo(sb + SM_XA, 57344);
#pragma unroll 1
      for (int i = 0; i < 7; i++) mbar_wait(bar + 8 * (B_FULLXA + i), 1);
      uint32_t done = 0;
#pragma unroll 1
      for (int i = 0; i < 8; i++) {
        const int n = 21 + i;
        mbar_wait(bar + 8 * (B_FULLWA + (n & 3)), (n >> 2) & 1);
        uint32_t c;
        asm volatile("ld.shared.u32 %0, [%1];" : "=r"(c) : "r"(sb + SM_ORDER + 32 + 4 * i) : "memory");
        c = __shfl_sync(0xffffffffu, c, 0);
        const uint32_t wc = wo + (c < 7 ? c * 448 : 3072);
#pragma unroll
        for (int kk = 0; kk < 4; kk++) {
          if (!(kk & 1)) wg_fence();
          mma_n112_ss_tb(o, desc(oa + (n & 3) * 512 + kk * 2), desc(wc + kk * 128), kk ? 1 : i);
          if (kk & 1) { wg_commit(); wg_wait<0>(); }
        }
        mbar_arrive_if(bar + 8 * (B_EMPTYWA + (n & 3)), t == 0);
        done |= 1u << c;
        mbar_arrive_if(bar + 8 * (B_EMPTYXA - 1) + 8 * c, t == 0 && ((done << 1) >> c & 1));
        mbar_arrive_if(bar + 8 * B_EMPTYXA + 8 * c, t == 32 && (done >> (c + 1) & 1));
      }
      pin(o);
#pragma unroll
      for (int m = 0; m < 2; m++) {
        uint32_t v[14];
#pragma unroll
        for (int i = 0; i < 14; i++) v[i] = pack_b(o[28 * m + 2 * i], o[28 * m + 2 * i + 1]);
        stage56(sb + SM_WA + m * 7168 + warp * (16 * 112), v, lane);
      }
      __syncwarp();
#pragma unroll
      for (int m = 0; m < 2; m++)
        copy_out56(P.outp + (size_t)(G * 64 + warp * 16) * 112 + cg * 14 + m * 7, sb + SM_WA + m * 7168 + warp * (16 * 112), lane);
    }
  }
}

typedef CUresult (*EncodeFn)(CUtensorMap*, CUtensorMapDataType, cuuint32_t, void*, const cuuint64_t*, const cuuint64_t*,
                             const cuuint32_t*, const cuuint32_t*, CUtensorMapInterleave, CUtensorMapSwizzle,
                             CUtensorMapL2promotion, CUtensorMapFloatOOBfill);

void make_map(EncodeFn enc, CUtensorMap* m, const void* ptr, uint64_t rows, uint64_t cols, uint32_t box_rows) {
  cuuint64_t dims[2] = {cols, rows};
  cuuint64_t strides[1] = {cols * 2};
  cuuint32_t box[2] = {64, box_rows};
  cuuint32_t es[2] = {1, 1};
  enc(m, CU_TENSOR_MAP_DATA_TYPE_BFLOAT16, 2, const_cast<void*>(ptr), dims, strides, box, es,
      CU_TENSOR_MAP_INTERLEAVE_NONE, CU_TENSOR_MAP_SWIZZLE_128B,
      CU_TENSOR_MAP_L2_PROMOTION_L2_128B,
      CU_TENSOR_MAP_FLOAT_OOB_FILL_NONE);
}

}

extern "C" void kernel_launch(void* const* d_in, const int* in_sizes, int n_in, void* d_out, int out_size) {
  static EncodeFn enc = nullptr;
  static void *kv, *oA, *oB, *kvf, *part, *stats, *flags, *epoch;
  if (!enc) {
    void* fn = nullptr;
    cudaDriverEntryPointQueryResult q;
    cudaGetDriverEntryPoint("cuTensorMapEncodeTiled", &fn, cudaEnableDefault, &q);
    enc = (EncodeFn)fn;
    cudaGetSymbolAddress(&kv, g_kv);
    cudaGetSymbolAddress(&oA, g_oA);
    cudaGetSymbolAddress(&oB, g_oB);
    cudaGetSymbolAddress(&kvf, g_kvf);
    cudaGetSymbolAddress(&part, g_part);
    cudaGetSymbolAddress(&stats, g_stats);
    cudaGetSymbolAddress(&flags, g_flags);
    cudaGetSymbolAddress(&epoch, g_epoch);
    cudaFuncSetAttribute(fused_kernel, cudaFuncAttributeMaxDynamicSharedMemorySize, SMEM_BYTES);
  }
  Params P;
  make_map(enc, &P.xA, d_in[0], S_LEN, DM, 128);
  make_map(enc, &P.wA, d_in[1], DM, 3 * DM, 64);
  make_map(enc, &P.woA, d_in[2], DM, DM, 64);
  make_map(enc, &P.xB, d_in[3], S_LEN, DM, 128);
  make_map(enc, &P.wBh, d_in[4], DM, 3 * DM, 32);
  make_map(enc, &P.woB, d_in[5], DM, DM, 64);
  make_map(enc, &P.kv, kv, 16 * S_LEN, 64, 64);
  make_map(enc, &P.oA, oA, S_LEN, 512, 64);
  make_map(enc, &P.oB, oB, S_LEN, 512, 64);
  P.xBp = (const __nv_bfloat16*)d_in[3];
  P.wBp = (const __nv_bfloat16*)d_in[4];
  P.part = (uint4*)part;
  P.kvf = (uint2*)kvf;
  P.oBp = (uint4*)oB;
  P.outp = (uint4*)d_out;
  P.stats = (unsigned long long*)stats;
  P.flags = (unsigned*)flags;
  P.epoch = (unsigned*)epoch;
  P.zero = 0;
  fused_kernel<<<128, 512, SMEM_BYTES>>>(P);
}
```
